```python
import torch

def _softmax(x, axis=-1):
    return torch.softmax(x, dim=axis)
def _gelu(x):
    return torch.nn.functional.gelu(x, approximate="tanh")
def _silu(x):
    return torch.nn.functional.silu(x)
def _sigmoid(x):
    return torch.sigmoid(x)
def _layernorm(x, axis=-1, eps=1e-5):
    m = x.mean(dim=axis, keepdim=True)
    v = x.var(dim=axis, keepdim=True, unbiased=False)
    return (x - m) / torch.sqrt(v + eps)
def _scatter_add(tgt, idx, src, axis=0):
    return tgt.clone().index_add_(axis, idx, src)
def _segment_sum(src, seg, n):
    out = torch.zeros((n,) + src.shape[1:], dtype=src.dtype)
    return out.index_add_(0, seg, src)
def _pad(x, pw):
    flat = tuple(v for pair in reversed(pw) for v in pair)
    return torch.nn.functional.pad(x, flat)

kernel_name = 'gated_mix__mha_block_cached__glu_gated_glu__decode'

def setup_inputs():

    _w = (lambda a: (lambda t: t.to(torch.bfloat16) if t.is_floating_point() else t)(torch.as_tensor(a)))
    def _A_setup():
        B, Sq, D = 2, 1, 448
        H, Sk, Dh = 16, 8192, 256
        return {
            "x": _w((lambda *s: torch.randn(*s, dtype=torch.bfloat16) * 0.05)(B, Sq, D)),
            "k_cache": _w((lambda *s: torch.randn(*s, dtype=torch.bfloat16) * 6.4)(B, H, Sk, Dh)),
            "v_cache": _w((lambda *s: torch.randn(*s, dtype=torch.bfloat16) * 0.4)(B, H, Sk, Dh)),
            "wq": _w((lambda *s: torch.randn(*s, dtype=torch.bfloat16) * 6.4)(D, H * Dh) * (D ** -0.5)),
            "wo": _w((lambda *s: torch.randn(*s, dtype=torch.bfloat16) * 0.4)(H * Dh, D) * ((H * Dh) ** -0.5)),
        }
    _A_in = _A_setup()

    def _B_setup():
        B, S, D, F = 2, 1, 448, 1792
        return {
            "x": _w((lambda *s: torch.randn(*s, dtype=torch.bfloat16) * 0.05)(B, S, D)),
            "w_gate": _w((lambda *s: torch.randn(*s, dtype=torch.bfloat16) * 0.4)(D, F)),
            "w_up": _w((lambda *s: torch.randn(*s, dtype=torch.bfloat16) * 0.05)(D, F)),
            "w_down": _w((lambda *s: torch.randn(*s, dtype=torch.bfloat16) * 0.05)(F, D)),
        }
    _B_in = _B_setup()

    return {
        "A_x": _A_in["x"],
        "A_k_cache": _A_in["k_cache"],
        "A_v_cache": _A_in["v_cache"],
        "A_wq": _A_in["wq"],
        "A_wo": _A_in["wo"],
        "B_x": _B_in["x"],
        "B_w_gate": _B_in["w_gate"],
        "B_w_up": _B_in["w_up"],
        "B_w_down": _B_in["w_down"],
        "gate_w": _w((lambda *s: torch.randn(*s, dtype=torch.bfloat16) * 0.05)(448) * 16.0),
    }

def reference(A_x, A_k_cache, A_v_cache, A_wq, A_wo, B_x, B_w_gate, B_w_up, B_w_down, gate_w):
    def _A_ref(x, k_cache, v_cache, wq, wo):
        B, Sq, D = x.shape
        H, Dh = 16, 256
        q = (lambda x, *d: x.permute(*d))((x @ wq).reshape(B, Sq, H, Dh), 0, 2, 1, 3)
        scores = torch.einsum("bhqd,bhkd->bhqk", q, k_cache) * (Dh ** -0.5)
        p = _softmax(scores, axis=-1)
        o = torch.einsum("bhqk,bhkd->bhqd", p, v_cache)
        return (lambda x, *d: x.permute(*d))(o, 0, 2, 1, 3).reshape(B, Sq, H * Dh) @ wo

    def _B_ref(x, w_gate, w_up, w_down):
        g = torch.einsum("bsd,df->bsf", x, w_gate)
        u = torch.einsum("bsd,df->bsf", x, w_up)
        h = _sigmoid(g) * u
        return torch.einsum("bsf,fd->bsd", h, w_down)

    x = A_x
    g = _sigmoid((x * gate_w).sum(-1, keepdims=True))
    a = _A_ref(x, A_k_cache, A_v_cache, A_wq, A_wo)
    b = _B_ref(x, B_w_gate, B_w_up, B_w_down)
    return g * a + (1 - g) * b
```

```cpp
#include <cuda.h>
#include <cuda_runtime.h>
#include <cuda_bf16.h>
#include <stdint.h>

namespace {

constexpr int kB = 2, kH = 16, kSK = 8192, kDH = 256, kD = 448, kF = 1792;
constexpr int kHD = kH * kDH;
constexpr int kPairs = kB * kH;

#define P_KPW 2
#define P_NSTAGE 8
#define P_INFL 6

constexpr int NCW = 8;
constexpr int NCT = NCW * 32;
constexpr int NJW = 4;
constexpr int NJT = NJW * 32;
constexpr int NTHREADS = 32 + NJT + NCT;
constexpr int KPW = P_KPW;
constexpr int TK = NCW * KPW;
constexpr int TILE = TK * kDH * 2;
constexpr int IPP = kSK / TK;
constexpr int NITEMS = kPairs * IPP;
constexpr int NSTAGE = P_NSTAGE;
constexpr int INFL = P_INFL;
constexpr int NSTATIC = (INFL + 1) / 2;
constexpr int MAXG = 144;
constexpr int NQJOB = 128;
constexpr int NOJOB = 128;
constexpr int NGJOB = 112;
constexpr int RK = (MAXG + 31) / 32;
constexpr int DK = MAXG / 16;
#define P_FREE_BACK 0
#define P_WQ_FIRST 0
#define P_EAGER 31
#define P_PROMO CU_TENSOR_MAP_L2_PROMOTION_L2_128B
#define P_GPACE 1
#define P_GSTEP 2
#define P_TDEPTH 1
constexpr int TDEPTH = P_TDEPTH;
#define P_JLAG 2
#define P_JEND 32
#define P_BACKOFF 0
constexpr unsigned FREE_ITEM = NITEMS - P_FREE_BACK / TK;
constexpr unsigned SPIN_LIMIT = 1u << 24;

static_assert(2 * NSTAGE >= INFL, "ring too small");

constexpr int SM_RING = 0;
constexpr int SM_WO = SM_RING + NSTAGE * 2 * TILE;
constexpr int SM_Q = SM_WO + 32 * kD * 2;
constexpr int SM_FL = SM_Q + kPairs * kDH * 4;
constexpr int SM_X = SM_FL + 2 * NCW * kDH * 4;
constexpr int SM_ML = SM_X + kD * 8;
constexpr int SM_JS = SM_ML + 2 * NCW * 2 * 4;
constexpr int SM_MISC = SM_JS + 2 * NJW * 64 * 4;
constexpr int SM_BAR = SM_MISC + 64;
constexpr int SM_TOTAL = SM_BAR + 8 * (3 * NSTAGE + 3) + 4 * NSTAGE;
static_assert(SM_TOTAL <= 232448, "shared memory budget");
static_assert(2 * TILE >= 16 * kD * 2 && NSTAGE >= 3, "GLU slices are staged in ring stages");

__device__ unsigned g_epoch;
__device__ unsigned g_ticket;
__device__ unsigned g_done;
__device__ __align__(16) unsigned long long g_q[kPairs * (kDH / 2)];
__device__ unsigned g_init[MAXG];
__device__ __align__(32) uint32_t g_rec[kPairs * MAXG * 8];
__device__ __align__(16) uint32_t g_part[kPairs * MAXG * kDH];
__device__ __align__(16) uint32_t g_y[MAXG * kB * kD];

#define STAMP(i) do { } while (0)

__device__ __forceinline__ uint32_t smem_u32(const void* p) { return (uint32_t)__cvta_generic_to_shared(p); }
__device__ __forceinline__ void mbar_init(uint32_t bar, uint32_t cnt) {
    asm volatile("mbarrier.init.shared::cta.b64 [%0], %1;" ::"r"(bar), "r"(cnt) : "memory");
}
__device__ __forceinline__ void mbar_expect_tx(uint32_t bar, uint32_t bytes) {
    asm volatile("mbarrier.arrive.expect_tx.shared::cta.b64 _, [%0], %1;" ::"r"(bar), "r"(bytes) : "memory");
}
__device__ __forceinline__ void mbar_arrive(uint32_t bar) {
    asm volatile("mbarrier.arrive.shared::cta.b64 _, [%0];" ::"r"(bar) : "memory");
}
__device__ __forceinline__ bool mbar_try_wait(uint32_t bar, uint32_t parity) {
    uint32_t ok;
    asm volatile(
        "{\n.reg .pred p;\nmbarrier.try_wait.parity.shared::cta.b64 p, [%1], %2;\nselp.u32 %0, 1, 0, p;\n}"
        : "=r"(ok) : "r"(bar), "r"(parity) : "memory");
    return ok != 0;
}
__device__ __forceinline__ void mbar_wait(uint32_t bar, uint32_t parity) {
    unsigned n = 0;
#pragma unroll 1
    while (!mbar_try_wait(bar, parity)) {
        if (++n > SPIN_LIMIT) __trap();
    }
}
__device__ __forceinline__ void mbar_wait_long(uint32_t bar, uint32_t parity) {
    unsigned n = 0;
#pragma unroll 1
    while (!mbar_try_wait(bar, parity)) {
        __nanosleep(64);
        if (++n > SPIN_LIMIT) __trap();
    }
}
__device__ __forceinline__ void bulk_g2s(uint32_t dst, const void* src, uint32_t bytes, uint32_t bar, uint64_t pol) {
    asm volatile(
        "cp.async.bulk.shared::cluster.global.mbarrier::complete_tx::bytes.L2::cache_hint [%0], [%1], %2, [%3], %4;"
        ::"r"(dst), "l"(src), "r"(bytes), "r"(bar), "l"(pol) : "memory");
}
__device__ __forceinline__ void tma_2d(uint32_t dst, const CUtensorMap* map, int c0, int c1, uint32_t bar, uint64_t pol) {
    asm volatile(
        "cp.async.bulk.tensor.2d.shared::cluster.global.mbarrier::complete_tx::bytes.L2::cache_hint [%0], [%1, {%2, %3}], [%4], %5;"
        ::"r"(dst), "l"(map), "r"(c0), "r"(c1), "r"(bar), "l"(pol) : "memory");
}
__device__ __forceinline__ void bar_sync(int id, int n) { asm volatile("bar.sync %0, %1;" ::"r"(id), "r"(n) : "memory"); }
__device__ __forceinline__ void bar_arrive(int id, int n) { asm volatile("barrier.arrive %0, %1;" ::"r"(id), "r"(n) : "memory"); }
__device__ __forceinline__ unsigned atom_inc(unsigned* p) {
    unsigned v;
    asm volatile("atom.relaxed.gpu.global.add.u32 %0, [%1], 1;" : "=r"(v) : "l"(p) : "memory");
    return v;
}
__device__ __forceinline__ uint4 ldg_nc(const void* p) {
    uint4 v;
    asm volatile("ld.global.nc.L1::no_allocate.v4.u32 {%0,%1,%2,%3}, [%4];" : "=r"(v.x), "=r"(v.y), "=r"(v.z), "=r"(v.w) : "l"(p));
    return v;
}
__device__ __forceinline__ float ldg_bf(const __nv_bfloat16* p) {
    unsigned short v;
    asm volatile("ld.global.nc.u16 %0, [%1];" : "=h"(v) : "l"(p));
    return __uint_as_float((uint32_t)v << 16);
}
__device__ __forceinline__ uint4 lds128(uint32_t a) {
    uint4 v;
    asm volatile("ld.shared.v4.u32 {%0,%1,%2,%3}, [%4];" : "=r"(v.x), "=r"(v.y), "=r"(v.z), "=r"(v.w) : "r"(a));
    return v;
}
__device__ __forceinline__ unsigned long long pack_ll(uint32_t v, uint32_t tag) {
    return ((unsigned long long)tag << 32) | v;
}
__device__ __forceinline__ void st_ll(unsigned long long* p, uint32_t v, uint32_t tag) {
    asm volatile("st.relaxed.gpu.global.b64 [%0], %1;" ::"l"(p), "l"(pack_ll(v, tag)) : "memory");
}
__device__ __forceinline__ void st_ll2(unsigned long long* p, uint32_t v0, uint32_t v1, uint32_t tag) {
    asm volatile("st.relaxed.gpu.global.v2.b64 [%0], {%1, %2};" ::"l"(p), "l"(pack_ll(v0, tag)), "l"(pack_ll(v1, tag)) : "memory");
}
__device__ __forceinline__ void ld_ll(unsigned long long& v, const unsigned long long* p, bool on) {
    asm volatile("{\n.reg .pred p;\nsetp.ne.u32 p, %2, 0;\n@p ld.relaxed.gpu.global.b64 %0, [%1];\n}"
                 : "+l"(v) : "l"(p), "r"((uint32_t)on) : "memory");
}
__device__ __forceinline__ void ld_ll2(unsigned long long& a, unsigned long long& b, const unsigned long long* p, bool on) {
    asm volatile("{\n.reg .pred p;\nsetp.ne.u32 p, %3, 0;\n@p ld.relaxed.gpu.global.v2.b64 {%0, %1}, [%2];\n}"
                 : "+l"(a), "+l"(b) : "l"(p), "r"((uint32_t)on) : "memory");
}
__device__ __forceinline__ void ld_w4(uint4& v, const uint32_t* p, bool on) {
    asm volatile("{\n.reg .pred p;\nsetp.ne.u32 p, %5, 0;\n@p ld.relaxed.gpu.global.v4.b32 {%0, %1, %2, %3}, [%4];\n}"
                 : "+r"(v.x), "+r"(v.y), "+r"(v.z), "+r"(v.w) : "l"(p), "r"((uint32_t)on) : "memory");
}
__device__ __forceinline__ void ld_w2(uint2& v, const uint32_t* p, bool on) {
    asm volatile("{\n.reg .pred p;\nsetp.ne.u32 p, %3, 0;\n@p ld.relaxed.gpu.global.v2.b32 {%0, %1}, [%2];\n}"
                 : "+r"(v.x), "+r"(v.y) : "l"(p), "r"((uint32_t)on) : "memory");
}
__device__ __forceinline__ void st_w4_zero(uint32_t* p, bool on) {
    asm volatile("{\n.reg .pred p;\nsetp.ne.u32 p, %1, 0;\n@p st.relaxed.gpu.global.v4.b32 [%0], {%2, %2, %2, %2};\n}"
                 ::"l"(p), "r"((uint32_t)on), "r"(0u) : "memory");
}
__device__ __forceinline__ uint32_t nz_bits(float v) {
    const uint32_t u = __float_as_uint(v);
    return u == 0u ? 0x80000000u : u;
}
__device__ __forceinline__ void st_w(uint32_t* p, float v) {
    asm volatile("st.relaxed.gpu.global.b32 [%0], %1;" ::"l"(p), "r"(nz_bits(v)) : "memory");
}
__device__ __forceinline__ void st_w2(uint32_t* p, float a, float b) {
    asm volatile("st.relaxed.gpu.global.v2.b32 [%0], {%1, %2};" ::"l"(p), "r"(nz_bits(a)), "r"(nz_bits(b)) : "memory");
}
__device__ __forceinline__ void st_w4(uint32_t* p, const float (&v)[4]) {
    asm volatile("st.relaxed.gpu.global.v4.b32 [%0], {%1, %2, %3, %4};" ::"l"(p), "r"(nz_bits(v[0])), "r"(nz_bits(v[1])),
                 "r"(nz_bits(v[2])), "r"(nz_bits(v[3])) : "memory");
}
__device__ __forceinline__ bool full4(const uint4& v) { return v.x != 0u && v.y != 0u && v.z != 0u && v.w != 0u; }
__device__ __forceinline__ uint32_t tag_of(unsigned long long v) { return (uint32_t)(v >> 32); }
__device__ __forceinline__ float val_of(unsigned long long v) { return __uint_as_float((uint32_t)v); }
__device__ __forceinline__ float bf_lo(uint32_t u) { return __uint_as_float(u << 16); }
__device__ __forceinline__ float bf_hi(uint32_t u) { return __uint_as_float(u & 0xffff0000u); }
__device__ __forceinline__ float bf_round(float x) { return __bfloat162float(__float2bfloat16_rn(x)); }
__device__ __forceinline__ float ex2(float x) {
    float y;
    asm("ex2.approx.ftz.f32 %0, %1;" : "=f"(y) : "f"(x));
    return y;
}
__device__ __forceinline__ float sigmoidf_(float x) { return __fdividef(1.0f, 1.0f + __expf(-x)); }

__device__ __forceinline__ void fma8(float (&acc)[8], const uint4& w, float s) {
    acc[0] = fmaf(s, bf_lo(w.x), acc[0]); acc[1] = fmaf(s, bf_hi(w.x), acc[1]);
    acc[2] = fmaf(s, bf_lo(w.y), acc[2]); acc[3] = fmaf(s, bf_hi(w.y), acc[3]);
    acc[4] = fmaf(s, bf_lo(w.z), acc[4]); acc[5] = fmaf(s, bf_hi(w.z), acc[5]);
    acc[6] = fmaf(s, bf_lo(w.w), acc[6]); acc[7] = fmaf(s, bf_hi(w.w), acc[7]);
}
__device__ __forceinline__ float dot8(const uint4& w, const float (&q)[8]) {
    float a = q[0] * bf_lo(w.x), b = q[1] * bf_hi(w.x);
    a = fmaf(q[2], bf_lo(w.y), a); b = fmaf(q[3], bf_hi(w.y), b);
    a = fmaf(q[4], bf_lo(w.z), a); b = fmaf(q[5], bf_hi(w.z), b);
    a = fmaf(q[6], bf_lo(w.w), a); b = fmaf(q[7], bf_hi(w.w), b);
    return a + b;
}

__device__ __forceinline__ void reduce16(const float (&a0)[8], const float (&a1)[8], int lane, float& r0, float& r1) {
    float a[8];
    const bool h4 = lane & 16, h3 = lane & 8, h2 = lane & 4;
#pragma unroll
    for (int i = 0; i < 8; i++) {
        float send = h4 ? a0[i] : a1[i], keep = h4 ? a1[i] : a0[i];
        a[i] = keep + __shfl_xor_sync(0xffffffffu, send, 16);
    }
    float b[4];
#pragma unroll
    for (int i = 0; i < 4; i++) {
        float send = h3 ? a[i] : a[i + 4], keep = h3 ? a[i + 4] : a[i];
        b[i] = keep + __shfl_xor_sync(0xffffffffu, send, 8);
    }
    {
        float s0 = h2 ? b[0] : b[2], k0 = h2 ? b[2] : b[0];
        float s1 = h2 ? b[1] : b[3], k1 = h2 ? b[3] : b[1];
        r0 = k0 + __shfl_xor_sync(0xffffffffu, s0, 4);
        r1 = k1 + __shfl_xor_sync(0xffffffffu, s1, 4);
    }
}

struct Params {
    const __nv_bfloat16* x;
    const __nv_bfloat16* kc;
    const __nv_bfloat16* vc;
    const __nv_bfloat16* wq;
    const __nv_bfloat16* wo;
    const __nv_bfloat16* wg;
    const __nv_bfloat16* wu;
    const __nv_bfloat16* wd;
    const __nv_bfloat16* gw;
    __nv_bfloat16* out;
};

__device__ __forceinline__ size_t item_offset(unsigned item) { return (size_t)item * (TK * kDH); }

__global__ void __launch_bounds__(NTHREADS, 1) fused_kernel(const Params P, const __grid_constant__ CUtensorMap map_g,
                                                           const __grid_constant__ CUtensorMap map_u) {
    extern __shared__ __align__(1024) unsigned char sm[];
    const int tid = threadIdx.x, lane = tid & 31, wid = tid >> 5;
    const int cta = blockIdx.x, G = gridDim.x;
    const uint32_t sbase = smem_u32(sm);
    const uint32_t barK = sbase + SM_BAR, barV = barK + 8 * NSTAGE, barE = barV + 8 * NSTAGE;
    const uint32_t barW = barE + 8 * NSTAGE, barG = barW + 8, barI = barG + 8;
    volatile int* s_item = (volatile int*)(sm + SM_BAR + 8 * (3 * NSTAGE + 3));
    float* s_misc = (float*)(sm + SM_MISC);
    volatile int* s_cur = (volatile int*)(s_misc + 1);
    volatile int* s_gst = (volatile int*)(s_misc + 6);
    const int gjob = cta >= NOJOB ? cta - NOJOB : (cta + (G - NOJOB) < NGJOB ? cta + (G - NOJOB) : -1);

    if (wid == 0) {
        if (lane != 0) return;
        STAMP(0);
#pragma unroll
        for (int s = 0; s < NSTAGE; s++) {
            mbar_init(barK + 8 * s, 1);
            mbar_init(barV + 8 * s, 1);
            mbar_init(barE + 8 * s, NCW);
        }
        mbar_init(barW, 1);
        mbar_init(barG, 1);
        mbar_init(barI, 1);
        asm volatile("fence.mbarrier_init.release.cluster;" ::: "memory");
        asm volatile("fence.proxy.async.shared::cta;" ::: "memory");
        uint64_t pol;
        asm volatile("createpolicy.fractional.L2::evict_first.b64 %0, 1.0;" : "=l"(pol));
#pragma unroll
        for (int i = 0; i < NSTATIC; i++) {
            const int item = i * G + cta;
            const size_t off = item_offset(item);
            s_item[i] = item;
            mbar_expect_tx(barK + 8 * i, TILE);
            bulk_g2s(sbase + SM_RING + i * 2 * TILE, P.kc + off, TILE, barK + 8 * i, pol);
            if (2 * i + 1 < INFL) {
                mbar_expect_tx(barV + 8 * i, TILE);
                bulk_g2s(sbase + SM_RING + i * 2 * TILE + TILE, P.vc + off, TILE, barV + 8 * i, pol);
            }
        }
        unsigned epoch;
        asm volatile("ld.relaxed.gpu.global.u32 %0, [%1];" : "=r"(epoch) : "l"(&g_epoch) : "memory");
        unsigned next[TDEPTH];
#pragma unroll
        for (int k = 0; k < TDEPTH; k++) next[k] = atom_inc(&g_ticket);
        s_misc[0] = __uint_as_float(epoch);
        *s_cur = 0;
        bar_arrive(1, NCT + 32);
        bar_arrive(3, NJT + 32);
        asm volatile("prefetch.tensormap [%0];" ::"l"(&map_g) : "memory");
        asm volatile("prefetch.tensormap [%0];" ::"l"(&map_u) : "memory");
        if (INFL & 1) {
            constexpr int i = NSTATIC - 1;
            mbar_wait(barK + 0, 0);
            const size_t off = item_offset(i * G + cta);
            mbar_expect_tx(barV + 8 * i, TILE);
            bulk_g2s(sbase + SM_RING + i * 2 * TILE + TILE, P.vc + off, TILE, barV + 8 * i, pol);
        }
        bool wo_issued = cta >= NOJOB;
        const unsigned wo_item = (unsigned)max((cta >> 3) - 1, 2) * IPP;
#pragma unroll 1
        for (int i = NSTATIC;; i++) {
            const int s = i % NSTAGE;
            if (i >= NSTAGE) mbar_wait(barE + 8 * s, ((i / NSTAGE) - 1) & 1);
            const unsigned item = next[0] + NSTATIC * G;
            if (item < FREE_ITEM) {
                const int n = 2 * i - INFL, j = n >> 1;
                mbar_wait(((n & 1) ? barV : barK) + 8 * (j % NSTAGE), (j / NSTAGE) & 1);
            }
            if (item >= (unsigned)NITEMS) {
                s_item[s] = -1;
                mbar_arrive(barK + 8 * s);
                STAMP(3);
                if (gjob >= 0) {
                    *s_gst = s;
                    mbar_expect_tx(barG, 3 * 16 * kD * 2);
                    auto landed = [&](int n) {
                        n = min(n, 2 * i - 1);
                        if (n >= 0) mbar_wait(((n & 1) ? barV : barK) + 8 * ((n >> 1) % NSTAGE), ((n >> 1) / NSTAGE) & 1);
                    };
                    uint32_t dst = sbase + SM_RING + s * 2 * TILE;
                    landed(2 * i - INFL + P_GPACE);
                    tma_2d(dst, &map_g, gjob * 16, 0, barG, pol);
                    tma_2d(dst + 224 * 32, &map_g, gjob * 16, 224, barG, pol);
                    int s1 = (i + 1) % NSTAGE;
                    if (i + 1 >= NSTAGE) mbar_wait(barE + 8 * s1, (((i + 1) / NSTAGE) - 1) & 1);
                    dst = sbase + SM_RING + s1 * 2 * TILE;
                    landed(2 * i - INFL + P_GPACE + P_GSTEP);
                    tma_2d(dst, &map_u, gjob * 16, 0, barG, pol);
                    tma_2d(dst + 224 * 32, &map_u, gjob * 16, 224, barG, pol);
                    s1 = (i + 2) % NSTAGE;
                    if (i + 2 >= NSTAGE) mbar_wait(barE + 8 * s1, (((i + 2) / NSTAGE) - 1) & 1);
                    landed(2 * i - INFL + P_GPACE + 2 * P_GSTEP);
                    bulk_g2s(sbase + SM_RING + s1 * 2 * TILE, P.wd + (size_t)gjob * 16 * kD, 16 * kD * 2, barG, pol);
                }
                break;
            }
            const size_t off = item_offset(item);
            s_item[s] = (int)item;
            mbar_expect_tx(barK + 8 * s, TILE);
            bulk_g2s(sbase + SM_RING + s * 2 * TILE, P.kc + off, TILE, barK + 8 * s, pol);
#pragma unroll
            for (int k = 0; k + 1 < TDEPTH; k++) next[k] = next[k + 1];
            next[TDEPTH - 1] = atom_inc(&g_ticket);
            if (!wo_issued && item >= wo_item) {
                wo_issued = true;
                mbar_expect_tx(barW, 32 * kD * 2);
                bulk_g2s(sbase + SM_WO, P.wo + (size_t)cta * 32 * kD, 32 * kD * 2, barW, pol);
            }
            if (item < FREE_ITEM) {
                const int n = 2 * i + 1 - INFL, j = n >> 1;
                mbar_wait(((n & 1) ? barV : barK) + 8 * (j % NSTAGE), (j / NSTAGE) & 1);
            }
            mbar_expect_tx(barV + 8 * s, TILE);
            bulk_g2s(sbase + SM_RING + s * 2 * TILE + TILE, P.vc + off, TILE, barV + 8 * s, pol);
        }
        if (!wo_issued) {
            mbar_expect_tx(barW, 32 * kD * 2);
            bulk_g2s(sbase + SM_WO, P.wo + (size_t)cta * 32 * kD, 32 * kD * 2, barW, pol);
        }
        if (next[TDEPTH - 1] == 0xffffffffu) __trap();
        if (atom_inc(&g_done) == (unsigned)G - 1) {
            g_ticket = 0;
            g_done = 0;
            g_epoch = epoch + 1;
        }
        return;
    }

    if (wid <= NJW) {
        const int jt = tid - 32, jw = wid - 1;
        float* s_js = (float*)(sm + SM_JS);
        const int gc = min(jw * 16 + (lane & 15), kD / 8 - 1), gh = lane >> 4;
        const bool gc_ok = jw * 16 + (lane & 15) < kD / 8;
        float2* s_x = (float2*)(sm + SM_X);
#pragma unroll
        for (int i = 0; i < 4; i++)
            if (i * NJT + jt < kD) s_x[i * NJT + jt] = make_float2(ldg_bf(P.x + i * NJT + jt), ldg_bf(P.x + kD + i * NJT + jt));
        if (jw < 2) {
            float s = 0.f;
#pragma unroll
            for (int i = 0; i < kD / 32; i++)
                s += bf_round(ldg_bf(P.x + jw * kD + i * 32 + lane) * ldg_bf(P.gw + i * 32 + lane));
#pragma unroll
            for (int o = 16; o; o >>= 1) s += __shfl_xor_sync(0xffffffffu, s, o);
            const float g0 = bf_round(sigmoidf_(bf_round(s)));
            if (lane == 0) { s_misc[2 + jw] = g0; s_misc[4 + jw] = bf_round(1.0f - g0); }
        }
        bar_sync(3, NJT + 32);
        const uint32_t tag = __float_as_uint(s_misc[0]) + 1u;
        const int r4 = lane >> 3, c8 = lane & 7;
        unsigned live = 0;
#pragma unroll
        for (int k = 0; k < DK; k++)
            if (k * 16 + jw * 4 + r4 < G) live |= 1u << k;
        st_w4_zero(&g_y[(size_t)cta * (kB * kD) + jt * 4], true);
        st_w4_zero(&g_y[(size_t)cta * (kB * kD) + (NJT + jt) * 4], NJT + jt < kB * kD / 4);
        st_w4_zero(&g_rec[((jt >> 1) * MAXG + cta) * 8 + (jt & 1) * 4], jt < 2 * kPairs);
#pragma unroll
        for (int i = jt; i < (kPairs - P_EAGER) * 64; i += NJT)
            st_w4_zero(&g_part[((size_t)(P_EAGER + (i >> 6)) * MAXG + cta) * kDH + (i & 63) * 4], true);
        bar_sync(4, NJT);
        if (jt == 0) {
            asm volatile("fence.acq_rel.gpu;" ::: "memory");
            asm volatile("st.relaxed.gpu.global.u32 [%0], %1;" ::"l"(&g_init[cta]), "r"(tag) : "memory");
            mbar_arrive(barI);
        }
        {
            unsigned n = 0;
            while (*s_cur < 1) {
                __nanosleep(200);
                if (++n > SPIN_LIMIT) __trap();
            }
#pragma unroll 1
            for (n = 0;; n++) {
                bool ok = true;
#pragma unroll
                for (int k = 0; k < RK; k++) {
                    unsigned v = tag;
                    if (k * 32 + lane < G)
                        asm volatile("ld.relaxed.gpu.global.u32 %0, [%1];" : "=r"(v) : "l"(&g_init[k * 32 + lane]) : "memory");
                    ok = ok && v == tag;
                }
                if (__all_sync(0xffffffffu, ok)) break;
                __nanosleep(500);
                if (n > SPIN_LIMIT) __trap();
            }
            asm volatile("fence.acq_rel.gpu;" ::: "memory");
        }
        float y0[4] = {}, y1[4] = {};
#pragma unroll 1
        for (int jb = 0; jb < (cta < NOJOB ? 2 : 0); jb++) {
            {
                const int jp = jb * kH + (cta >> 3);
                {
                    unsigned n = 0;
                    while (*s_cur < min(jp + P_JLAG, P_JEND)) {
                        __nanosleep(100);
                        if (++n > SPIN_LIMIT) __trap();
                    }
                }
                if (jt == 0) STAMP(9 + jb * 3);
                const uint32_t* rp = &g_rec[(jp * MAXG + lane) * 8];
                uint32_t* pp = &g_part[((size_t)jp * MAXG + jw * 4 + r4) * kDH + (cta & 7) * 32 + c8 * 4];
                uint2 rec[RK];
                uint4 dv[DK];
                unsigned need = live;
                unsigned known = jp >= P_EAGER ? live : 0u;
#pragma unroll
                for (int k = 0; k < RK; k++)
                    rec[k] = k * 32 + lane < G ? make_uint2(0u, 0u) : make_uint2(0xff800000u, 0x80000000u);
#pragma unroll
                for (int k = 0; k < DK; k++) dv[k] = make_uint4(0u, 0u, 0u, 0u);
#pragma unroll 1
                for (unsigned n = 0;; n++) {
#pragma unroll
                    for (int k = 0; k < RK; k++) ld_w2(rec[k], rp + k * 32 * 8, rec[k].x == 0u || rec[k].y == 0u);
#pragma unroll
                    for (int k = 0; k < DK; k++)
                        ld_w4(dv[k], pp + (size_t)k * 16 * kDH, (((need & known) >> k) & 1) && !full4(dv[k]));
                    bool ok = true;
#pragma unroll
                    for (int k = 0; k < RK; k++) {
                        const bool rok = rec[k].x != 0u && rec[k].y != 0u;
                        const unsigned seen = __ballot_sync(0xffffffffu, rok) >> (jw * 4 + r4);
                        const unsigned dead = __ballot_sync(0xffffffffu, rec[k].x == 0xff800000u) >> (jw * 4 + r4);
                        known |= ((seen & 1u) | ((seen >> 15) & 2u)) << (2 * k);
                        need &= ~(((dead & 1u) | ((dead >> 15) & 2u)) << (2 * k));
                        ok = ok && rok;
                    }
#pragma unroll
                    for (int k = 0; k < DK; k++) ok = ok && (!((need >> k) & 1) || full4(dv[k]));
                    if (__all_sync(0xffffffffu, ok)) break;
                    if (P_BACKOFF) __nanosleep(P_BACKOFF);
                    if (n > SPIN_LIMIT) __trap();
                }
                if (jt == 0) STAMP(10 + jb * 3);
                float M = __uint_as_float(rec[0].x);
#pragma unroll
                for (int k = 1; k < RK; k++) M = fmaxf(M, __uint_as_float(rec[k].x));
#pragma unroll
                for (int x = 16; x; x >>= 1) M = fmaxf(M, __shfl_xor_sync(0xffffffffu, M, x));
                float wt[RK], L = 0.f, a0 = 0.f, a1 = 0.f, a2 = 0.f, a3 = 0.f;
#pragma unroll
                for (int k = 0; k < RK; k++) {
                    wt[k] = ex2(__uint_as_float(rec[k].x) - M);
                    L = fmaf(wt[k], __uint_as_float(rec[k].y), L);
                }
#pragma unroll
                for (int k = 0; k < DK; k++) {
                    const float wk = __shfl_sync(0xffffffffu, wt[k >> 1], (k & 1) * 16 + jw * 4 + r4);
                    a0 = fmaf(wk, __uint_as_float(dv[k].x), a0);
                    a1 = fmaf(wk, __uint_as_float(dv[k].y), a1);
                    a2 = fmaf(wk, __uint_as_float(dv[k].z), a2);
                    a3 = fmaf(wk, __uint_as_float(dv[k].w), a3);
                }
#pragma unroll
                for (int x = 8; x <= 16; x <<= 1) {
                    a0 += __shfl_xor_sync(0xffffffffu, a0, x); a1 += __shfl_xor_sync(0xffffffffu, a1, x);
                    a2 += __shfl_xor_sync(0xffffffffu, a2, x); a3 += __shfl_xor_sync(0xffffffffu, a3, x);
                }
                float* js = s_js + (jb ^ 1) * (NJW * 64);
                if (lane < 8) *(float4*)&js[jw * 32 + lane * 4] = make_float4(a0, a1, a2, a3);
#pragma unroll
                for (int x = 16; x; x >>= 1) L += __shfl_xor_sync(0xffffffffu, L, x);
                bar_sync(4, NJT);
                if (jt == 0) STAMP(5);
                float acc = 0.f;
#pragma unroll
                for (int i = 0; i < NJW; i++) acc += js[i * 32 + lane];
                const float ov = bf_round(__fdividef(acc, L)) * s_misc[2 + jb];
                mbar_wait(barW, 0);
                float t[8] = {};
                const uint32_t wa = sbase + SM_WO + gh * 16 * (kD * 2) + gc * 16;
#pragma unroll
                for (int r = 0; r < 16; r++) fma8(t, lds128(wa + r * (kD * 2)), __shfl_sync(0xffffffffu, ov, gh * 16 + r));
                float y[4];
#pragma unroll
                for (int i = 0; i < 4; i++) {
                    const float send = gh ? t[i] : t[i + 4], keep = gh ? t[i + 4] : t[i];
                    y[i] = keep + __shfl_xor_sync(0xffffffffu, send, 16);
                }
#pragma unroll
                for (int i = 0; i < 4; i++) { y1[i] = y[i]; if (jb == 0) y0[i] = y[i]; }
                if (gjob < 0 && gc_ok) st_w4(&g_y[(size_t)cta * (kB * kD) + jb * kD + gc * 8 + gh * 4], y);
#pragma unroll
                for (int k = 0; k < DK; k++) st_w4_zero(pp + (size_t)k * 16 * kDH, jp < P_EAGER && ((need >> k) & 1));
            }
            if (jt == 0) STAMP(6);
            if (jt == 0) STAMP(11 + jb * 3);
        }
        if (gjob >= 0) {
            const int rg = jt >> 2, ch = jt & 3;
            mbar_wait_long(barG, 0);
            const int gs = *s_gst;
            float a0[8] = {}, a1[8] = {};
            const uint32_t ga = sbase + SM_RING + ((gs + (ch >> 1)) % NSTAGE) * 2 * TILE + rg * 32 + (ch & 1) * 16;
#pragma unroll
            for (int k = 0; k < 14; k++) {
                const float2 xv = s_x[k * 32 + rg];
                const uint4 wv = lds128(ga + k * 32 * 32);
                fma8(a0, wv, xv.x);
                fma8(a1, wv, xv.y);
            }
            uint4 wd[8];
#pragma unroll
            for (int f = 0; f < 8; f++) wd[f] = lds128(sbase + SM_RING + ((gs + 2) % NSTAGE) * 2 * TILE + (gh * 8 + f) * (kD * 2) + gc * 16);
            float r0, r1;
            reduce16(a0, a1, lane, r0, r1);
            float* js = s_js + NJW * 64;
            const int slot = (lane >> 4) * 32 + ch * 8 + ((lane >> 3) & 1) * 4 + ((lane >> 2) & 1) * 2;
            *(float2*)&js[jw * 64 + slot] = make_float2(r0, r1);
            bar_sync(4, NJT);
            const int o = (lane >> 4) * 32 + (lane & 15);
            float g = 0.f, u = 0.f;
#pragma unroll
            for (int i = 0; i < NJW; i++) { g += js[i * 64 + o]; u += js[i * 64 + o + 16]; }
            const float hv = bf_round(bf_round(sigmoidf_(bf_round(g))) * bf_round(u)) * s_misc[4 + (lane >> 4)];
#pragma unroll
            for (int i = 0; i < 8; i++) { a0[i] = 0.f; a1[i] = 0.f; }
#pragma unroll
            for (int f = 0; f < 8; f++) {
                fma8(a0, wd[f], __shfl_sync(0xffffffffu, hv, gh * 8 + f));
                fma8(a1, wd[f], __shfl_sync(0xffffffffu, hv, 16 + gh * 8 + f));
            }
#pragma unroll
            for (int i = 0; i < 4; i++) {
                const float s0 = gh ? a0[i] : a0[i + 4], k0 = gh ? a0[i + 4] : a0[i];
                const float s1 = gh ? a1[i] : a1[i + 4], k1 = gh ? a1[i + 4] : a1[i];
                y0[i] += k0 + __shfl_xor_sync(0xffffffffu, s0, 16);
                y1[i] += k1 + __shfl_xor_sync(0xffffffffu, s1, 16);
            }
            if (gc_ok) {
                st_w4(&g_y[(size_t)cta * (kB * kD) + gc * 8 + gh * 4], y0);
                st_w4(&g_y[(size_t)cta * (kB * kD) + kD + gc * 8 + gh * 4], y1);
            }
            if (jt == 0) STAMP(8);
            constexpr int YK = (MAXG + 63) / 64;
            uint32_t* yp = &g_y[(size_t)(jt >> 1) * (kB * kD) + gjob * 8 + (jt & 1) * 4];
            uint4 dv[YK];
#pragma unroll
            for (int k = 0; k < YK; k++) {
                const uint32_t z = k * 64 + (jt >> 1) < G ? 0u : 0x80000000u;
                dv[k] = make_uint4(z, z, z, z);
            }
#pragma unroll 1
            for (unsigned n = 0;; n++) {
#pragma unroll
                for (int k = 0; k < YK; k++) ld_w4(dv[k], yp + (size_t)k * 64 * (kB * kD), !full4(dv[k]));
                bool ok = true;
#pragma unroll
                for (int k = 0; k < YK; k++) ok = ok && full4(dv[k]);
                if (__all_sync(0xffffffffu, ok)) break;
                if (n > SPIN_LIMIT) __trap();
            }
            if (jt == 0) STAMP(15);
            float f0 = 0.f, f1 = 0.f, f2 = 0.f, f3 = 0.f;
#pragma unroll
            for (int k = 0; k < YK; k++) {
                f0 += __uint_as_float(dv[k].x); f1 += __uint_as_float(dv[k].y);
                f2 += __uint_as_float(dv[k].z); f3 += __uint_as_float(dv[k].w);
            }
            {
                const bool h4 = lane & 16, h3 = lane & 8;
                const float u0 = (h4 ? f2 : f0) + __shfl_xor_sync(0xffffffffu, h4 ? f0 : f2, 16);
                const float u1 = (h4 ? f3 : f1) + __shfl_xor_sync(0xffffffffu, h4 ? f1 : f3, 16);
                float v = (h3 ? u1 : u0) + __shfl_xor_sync(0xffffffffu, h3 ? u0 : u1, 8);
                v += __shfl_xor_sync(0xffffffffu, v, 4);
                v += __shfl_xor_sync(0xffffffffu, v, 2);
                if ((lane & 6) == 0) s_js[jw * 8 + (lane & 1) * 4 + (lane >> 4) * 2 + ((lane >> 3) & 1)] = v;
            }
            bar_sync(4, NJT);
            if (jt < 8) P.out[gjob * 8 + jt] = __float2bfloat16_rn((s_js[jt] + s_js[8 + jt]) + (s_js[16 + jt] + s_js[24 + jt]));
            if (jt == 0) STAMP(7);
        }
        return;
    }

    const int ct = tid - 32 - NJT, w = wid - 1 - NJW;
    float* s_fl = (float*)(sm + SM_FL);
    float* s_ml = (float*)(sm + SM_ML);
    float* s_q = (float*)(sm + SM_Q);

    {
        const int rg = ct >> 2, ch = ct & 3;
        float xv[2][7];
#pragma unroll
        for (int k = 0; k < 7; k++) {
            xv[0][k] = ldg_bf(P.x + rg + 64 * k);
            xv[1][k] = ldg_bf(P.x + kD + rg + 64 * k);
        }
        uint4 wv[7];
        const __nv_bfloat16* p = P.wq + (size_t)rg * kHD + (cta & (NQJOB - 1)) * 32 + ch * 8;
#pragma unroll
        for (int k = 0; k < 7; k++) wv[k] = ldg_nc(p + (size_t)k * 64 * kHD);
        float a0[8] = {}, a1[8] = {}, r0, r1;
#pragma unroll
        for (int k = 0; k < 7; k++) { fma8(a0, wv[k], xv[0][k]); fma8(a1, wv[k], xv[1][k]); }
        reduce16(a0, a1, lane, r0, r1);
        const int slot = (lane >> 4) * 32 + ch * 8 + ((lane >> 3) & 1) * 4 + ((lane >> 2) & 1) * 2;
        *(float2*)&s_fl[w * 64 + slot] = make_float2(r0, r1);
    }
    bar_sync(1, NCT + 32);
    if (ct == 0) STAMP(1);
    const uint32_t tag = __float_as_uint(s_misc[0]) + 1u;
    if (ct < 32 && cta < NQJOB) {
        float s0 = 0.f, s1 = 0.f;
#pragma unroll
        for (int i = 0; i < NCW; i++) {
            const float2 v = *(const float2*)&s_fl[i * 64 + 2 * ct];
            s0 += v.x; s1 += v.y;
        }
        const __nv_bfloat162 pk = __floats2bfloat162_rn(s0, s1);
        const int b = ct >> 4, h = cta >> 3;
        st_ll(&g_q[(b * kH + h) * (kDH / 2) + (cta & 7) * 16 + (ct & 15)], *(const uint32_t*)&pk, tag);
    }
    {
        constexpr float kScale = 0.0625f * 1.4426950408889634f;
        unsigned long long a[8], b[8];
#pragma unroll
        for (int i = 0; i < 8; i++) { a[i] = 0; b[i] = 0; }
#pragma unroll 1
        for (unsigned n = 0;; n++) {
#pragma unroll
            for (int i = 0; i < 8; i++)
                ld_ll2(a[i], b[i], &g_q[(i * NCT + ct) * 2], tag_of(a[i]) != tag || tag_of(b[i]) != tag);
            bool ok = true;
#pragma unroll
            for (int i = 0; i < 8; i++) ok = ok && tag_of(a[i]) == tag && tag_of(b[i]) == tag;
            if (ok) break;
            if (n > SPIN_LIMIT) __trap();
        }
#pragma unroll
        for (int i = 0; i < 8; i++) {
            const uint32_t x0 = (uint32_t)a[i], x1 = (uint32_t)b[i];
            *(float4*)&s_q[(i * NCT + ct) * 4] =
                make_float4(bf_lo(x0) * kScale, bf_hi(x0) * kScale, bf_lo(x1) * kScale, bf_hi(x1) * kScale);
        }
    }
    bar_sync(2, NCT);
    mbar_wait(barI, 0);
    if (ct == 0) STAMP(2);

    {
        float q[8], o[8], m = -INFINITY, l = 0.f;
        int cur = -1, next_rec = 0, fpar = 0;
#pragma unroll
        for (int j = 0; j < 8; j++) { q[j] = 0.f; o[j] = 0.f; }
        int s = 0;
        uint32_t ph = 0;
#pragma unroll 1
        for (;;) {
            mbar_wait(barK + 8 * s, ph);
            const int item = s_item[s];
            const int pair = item < 0 ? kPairs : item / IPP;
            if (pair != cur) {
                if (cur >= 0) {
                    float* fl = s_fl + fpar * (NCW * kDH);
                    float* ml = s_ml + fpar * (NCW * 2);
                    *(float4*)&fl[w * kDH + lane * 4] = make_float4(o[0], o[1], o[2], o[3]);
                    *(float4*)&fl[w * kDH + 128 + lane * 4] = make_float4(o[4], o[5], o[6], o[7]);
                    float lt = l;
#pragma unroll
                    for (int x = 16; x >= 32 / KPW; x >>= 1) lt += __shfl_xor_sync(0xffffffffu, lt, x);
                    if (lane == 0) *(float2*)&ml[w * 2] = make_float2(m, lt);
                    bar_sync(2, NCT);
                    float M = ml[0];
#pragma unroll
                    for (int i = 1; i < NCW; i++) M = fmaxf(M, ml[i * 2]);
                    float acc = 0.f, L = 0.f;
                    const int si = ((ct >> 2) & 1) * 128 + (ct >> 3) * 4 + (ct & 3);
#pragma unroll
                    for (int i = 0; i < NCW; i++) {
                        const float wt = ex2(ml[i * 2] - M);
                        acc = fmaf(wt, fl[i * kDH + si], acc);
                        L = fmaf(wt, ml[i * 2 + 1], L);
                    }
                    st_w(&g_part[((size_t)cur * MAXG + cta) * kDH + ct], acc);
                    if (ct == 0) st_w2(&g_rec[(cur * MAXG + cta) * 8], M, L);
                    fpar ^= 1;
                    next_rec = cur + 1;
                }
                if (next_rec + ct < pair)
                    st_w2(&g_rec[((next_rec + ct) * MAXG + cta) * 8], -INFINITY, 0.f);
                if (ct == 0) *s_cur = pair;
                if (item < 0) break;
                cur = pair;
                const float4 qa = *(const float4*)&s_q[pair * kDH + lane * 8];
                const float4 qb = *(const float4*)&s_q[pair * kDH + lane * 8 + 4];
                q[0] = qa.x; q[1] = qa.y; q[2] = qa.z; q[3] = qa.w;
                q[4] = qb.x; q[5] = qb.y; q[6] = qb.z; q[7] = qb.w;
                m = -INFINITY; l = 0.f;
#pragma unroll
                for (int j = 0; j < 8; j++) o[j] = 0.f;
            }
            const uint32_t kaddr = sbase + SM_RING + s * 2 * TILE + w * KPW * 512 + lane * 16;
            float sc[KPW];
#pragma unroll
            for (int k = 0; k < KPW; k++) sc[k] = dot8(lds128(kaddr + k * 512), q);
            {
                int width = KPW, x = 16;
#pragma unroll
                for (; width > 1; width >>= 1, x >>= 1) {
                    const bool hi = lane & x;
#pragma unroll
                    for (int k = 0; k < width / 2; k++) {
                        const float send = hi ? sc[k] : sc[k + width / 2];
                        const float keep = hi ? sc[k + width / 2] : sc[k];
                        sc[k] = keep + __shfl_xor_sync(0xffffffffu, send, x);
                    }
                }
#pragma unroll
                for (; x >= 1; x >>= 1) sc[0] += __shfl_xor_sync(0xffffffffu, sc[0], x);
            }
            float mx = sc[0];
#pragma unroll
            for (int x = 16; x >= 32 / KPW; x >>= 1) mx = fmaxf(mx, __shfl_xor_sync(0xffffffffu, mx, x));
            const float mn = fmaxf(m, mx);
            const float corr = ex2(m - mn);
            const float p = ex2(sc[0] - mn);
            m = mn;
            l = fmaf(l, corr, p);
#pragma unroll
            for (int j = 0; j < 8; j++) o[j] *= corr;
            float pk[KPW];
#pragma unroll
            for (int k = 0; k < KPW; k++) pk[k] = __shfl_sync(0xffffffffu, p, k * (32 / KPW));
            mbar_wait(barV + 8 * s, ph);
#pragma unroll
            for (int k = 0; k < KPW; k++) fma8(o, lds128(kaddr + TILE + k * 512), pk[k]);
            __syncwarp();
            if (lane == 0) mbar_arrive(barE + 8 * s);
            if (++s == NSTAGE) { s = 0; ph ^= 1; }
        }
    }

    if (ct == 0) STAMP(4);
    if (ct == NCT - 1) STAMP(25);
}

}

extern "C" void kernel_launch(void* const* d_in, const int* in_sizes, int n_in, void* d_out, int out_size) {
    (void)in_sizes; (void)n_in; (void)out_size;
    typedef CUresult (*EncodeFn)(CUtensorMap*, CUtensorMapDataType, cuuint32_t, void*, const cuuint64_t*, const cuuint64_t*,
                                 const cuuint32_t*, const cuuint32_t*, CUtensorMapInterleave, CUtensorMapSwizzle,
                                 CUtensorMapL2promotion, CUtensorMapFloatOOBfill);
    static EncodeFn encode = nullptr;
    static int grid = 0;
    if (grid == 0) {
        cudaDriverEntryPointQueryResult qr;
        void* fn = nullptr;
        cudaGetDriverEntryPoint("cuTensorMapEncodeTiled", &fn, cudaEnableDefault, &qr);
        encode = (EncodeFn)fn;
        int dev = 0, sms = 0;
        cudaGetDevice(&dev);
        cudaDeviceGetAttribute(&sms, cudaDevAttrMultiProcessorCount, dev);
        cudaFuncSetAttribute(fused_kernel, cudaFuncAttributeMaxDynamicSharedMemorySize, SM_TOTAL);
        grid = sms < MAXG ? sms : MAXG;
    }
    Params P;
    P.x = (const __nv_bfloat16*)d_in[0];
    P.kc = (const __nv_bfloat16*)d_in[1];
    P.vc = (const __nv_bfloat16*)d_in[2];
    P.wq = (const __nv_bfloat16*)d_in[3];
    P.wo = (const __nv_bfloat16*)d_in[4];
    P.wg = (const __nv_bfloat16*)d_in[6];
    P.wu = (const __nv_bfloat16*)d_in[7];
    P.wd = (const __nv_bfloat16*)d_in[8];
    P.gw = (const __nv_bfloat16*)d_in[9];
    P.out = (__nv_bfloat16*)d_out;
    CUtensorMap map_g, map_u;
    {
        const cuuint64_t dims[2] = {(cuuint64_t)kF, (cuuint64_t)kD};
        const cuuint64_t strides[1] = {(cuuint64_t)kF * 2};
        const cuuint32_t box[2] = {16, 224};
        const cuuint32_t es[2] = {1, 1};
        encode(&map_g, CU_TENSOR_MAP_DATA_TYPE_BFLOAT16, 2, (void*)P.wg, dims, strides, box, es, CU_TENSOR_MAP_INTERLEAVE_NONE,
               CU_TENSOR_MAP_SWIZZLE_NONE, P_PROMO, CU_TENSOR_MAP_FLOAT_OOB_FILL_NONE);
        encode(&map_u, CU_TENSOR_MAP_DATA_TYPE_BFLOAT16, 2, (void*)P.wu, dims, strides, box, es, CU_TENSOR_MAP_INTERLEAVE_NONE,
               CU_TENSOR_MAP_SWIZZLE_NONE, P_PROMO, CU_TENSOR_MAP_FLOAT_OOB_FILL_NONE);
    }
    fused_kernel<<<grid, NTHREADS, SM_TOTAL, cudaStreamPerThread>>>(P, map_g, map_u);
}
```

```cpp
#include <cuda.h>
#include <cuda_runtime.h>
#include <cuda_bf16.h>
#include <stdint.h>

namespace {

constexpr int kB = 2, kH = 16, kSK = 8192, kDH = 256, kD = 448, kF = 1792;
constexpr int kHD = kH * kDH;
constexpr int kPairs = kB * kH;

constexpr int NCW = 8;
constexpr int NCT = NCW * 32;
constexpr int NJW = 4;
constexpr int NJT = NJW * 32;
constexpr int NTHREADS = 32 + NJT + NCT;
constexpr int KPW = 2;
constexpr int TK = NCW * KPW;
constexpr int TILE = TK * kDH * 2;
constexpr int IPP = kSK / TK;
constexpr int NITEMS = kPairs * IPP;
constexpr int NSTAGE = 8;
constexpr int INFL = 5;
constexpr int NFIRST = (INFL + 1) / 2;
constexpr int NSTATIC = NSTAGE + 1;
constexpr int MAXG = 144;
constexpr int NOJOB = 128;
constexpr int NGJOB = 112;
constexpr int RK = (MAXG + 31) / 32;
constexpr int DK = MAXG / (4 * NJW);
constexpr int QF = NCT / 64;
constexpr int EAGER = kPairs - 1;
constexpr int JLAG = 2;
constexpr unsigned SPIN_LIMIT = 1u << 22;
constexpr float kScale = 0.0625f * 1.4426950408889634f;

static_assert((INFL & 1) && 2 * NSTAGE >= INFL + 1 && NSTATIC > NSTAGE, "ring configuration");

constexpr int SM_RING = 0;
constexpr int SM_W = SM_RING + NSTAGE * 2 * TILE;
constexpr int SM_Q = SM_W + 32 * kD * 2;
constexpr int SM_FL = SM_Q + kPairs * kDH * 4;
constexpr int SM_X = SM_FL + 2 * NCW * kDH * 4;
constexpr int SM_GW = SM_X + kB * kD * 2;
constexpr int SM_EP = SM_GW + kD * 2;
constexpr int SM_ML = SM_EP + 16;
constexpr int SM_JS = SM_ML + 2 * NCW * 2 * 4;
constexpr int SM_V = SM_JS + 2 * NJW * 64 * 4;
constexpr int SM_MISC = SM_V + 48 * 8;
constexpr int SM_BAR = SM_MISC + 32;
constexpr int NBAR = 3 * NSTAGE + 8;
constexpr int SM_ITEM = SM_BAR + 8 * NBAR;
constexpr int SM_TOTAL = SM_ITEM + 4 * NSTAGE;
static_assert(SM_TOTAL <= 232448, "shared memory budget");
static_assert(2 * TILE >= 16 * kD * 2, "the w_down slice is staged in a ring stage");

struct __align__(1024) Scratch {
    unsigned epoch[32];
    unsigned ticket[32];
    unsigned done[32];
    unsigned init[160];
    unsigned long long q[kPairs * (kDH / 2)];
    uint32_t rec[kPairs * MAXG * 8];
    uint32_t y[MAXG * kB * kD];
    uint32_t part[kPairs * MAXG * kDH];
};
__device__ Scratch g_s;
#define g_epoch g_s.epoch
#define g_ticket g_s.ticket
#define g_done g_s.done
#define g_init g_s.init
#define g_q g_s.q
#define g_rec g_s.rec
#define g_y g_s.y
__device__ __forceinline__ uint32_t* part_row(int pair, int cta) {
    return &g_s.part[((size_t)(kPairs - 1 - pair) * MAXG + cta) * kDH];
}

__device__ __forceinline__ uint32_t smem_u32(const void* p) { return (uint32_t)__cvta_generic_to_shared(p); }
__device__ __forceinline__ void mbar_init(uint32_t bar, uint32_t cnt) {
    asm volatile("mbarrier.init.shared::cta.b64 [%0], %1;" ::"r"(bar), "r"(cnt) : "memory");
}
__device__ __forceinline__ void mbar_expect_tx(uint32_t bar, uint32_t bytes) {
    asm volatile("mbarrier.arrive.expect_tx.shared::cta.b64 _, [%0], %1;" ::"r"(bar), "r"(bytes) : "memory");
}
__device__ __forceinline__ void mbar_arrive(uint32_t bar) {
    asm volatile("mbarrier.arrive.shared::cta.b64 _, [%0];" ::"r"(bar) : "memory");
}
__device__ __forceinline__ bool mbar_try_wait(uint32_t bar, uint32_t parity) {
    uint32_t ok;
    asm volatile(
        "{\n.reg .pred p;\nmbarrier.try_wait.parity.shared::cta.b64 p, [%1], %2;\nselp.u32 %0, 1, 0, p;\n}"
        : "=r"(ok) : "r"(bar), "r"(parity) : "memory");
    return ok != 0;
}
__device__ __forceinline__ void mbar_wait(uint32_t bar, uint32_t parity) {
    unsigned n = 0;
#pragma unroll 1
    while (!mbar_try_wait(bar, parity)) {
        if (++n > SPIN_LIMIT) __trap();
    }
}
__device__ __forceinline__ void wait_ge(const volatile int* p, int v, unsigned ns) {
    unsigned n = 0;
#pragma unroll 1
    while (*p < v) {
        __nanosleep(ns);
        if (++n > SPIN_LIMIT) __trap();
    }
}
__device__ __forceinline__ void fence_proxy_async() { asm volatile("fence.proxy.async.shared::cta;" ::: "memory"); }
__device__ __forceinline__ void bulk_g2s(uint32_t dst, const void* src, uint32_t bytes, uint32_t bar, uint64_t pol) {
    asm volatile(
        "cp.async.bulk.shared::cluster.global.mbarrier::complete_tx::bytes.L2::cache_hint [%0], [%1], %2, [%3], %4;"
        ::"r"(dst), "l"(src), "r"(bytes), "r"(bar), "l"(pol) : "memory");
}
__device__ __forceinline__ void bulk_g2s(uint32_t dst, const void* src, uint32_t bytes, uint32_t bar) {
    asm volatile("cp.async.bulk.shared::cluster.global.mbarrier::complete_tx::bytes [%0], [%1], %2, [%3];"
                 ::"r"(dst), "l"(src), "r"(bytes), "r"(bar) : "memory");
}
__device__ __forceinline__ void tma_2d(uint32_t dst, const CUtensorMap* map, int c0, int c1, uint32_t bar, uint64_t pol) {
    asm volatile(
        "cp.async.bulk.tensor.2d.shared::cluster.global.mbarrier::complete_tx::bytes.L2::cache_hint [%0], [%1, {%2, %3}], [%4], %5;"
        ::"r"(dst), "l"(map), "r"(c0), "r"(c1), "r"(bar), "l"(pol) : "memory");
}
__device__ __forceinline__ void bar_sync(int id, int n) { asm volatile("bar.sync %0, %1;" ::"r"(id), "r"(n) : "memory"); }
__device__ __forceinline__ unsigned atom_inc(unsigned* p) {
    unsigned v;
    asm volatile("atom.relaxed.gpu.global.inc.u32 %0, [%1], 0x7fffffff;" : "=r"(v) : "l"(p) : "memory");
    return v;
}
__device__ __forceinline__ uint4 lds128(uint32_t a) {
    uint4 v;
    asm volatile("ld.shared.v4.u32 {%0,%1,%2,%3}, [%4];" : "=r"(v.x), "=r"(v.y), "=r"(v.z), "=r"(v.w) : "r"(a));
    return v;
}
__device__ __forceinline__ float lds_bf(const unsigned char* base, int i) {
    return __uint_as_float((uint32_t)((const unsigned short*)base)[i] << 16);
}
__device__ __forceinline__ void st_ll(unsigned long long* p, uint32_t v, uint32_t tag) {
    asm volatile("st.relaxed.gpu.global.b64 [%0], %1;" ::"l"(p), "l"(((unsigned long long)tag << 32) | v) : "memory");
}
__device__ __forceinline__ void ld_ll2(unsigned long long& a, unsigned long long& b, const unsigned long long* p, bool on) {
    asm volatile("{\n.reg .pred p;\nsetp.ne.u32 p, %3, 0;\n@p ld.relaxed.gpu.global.v2.b64 {%0, %1}, [%2];\n}"
                 : "+l"(a), "+l"(b) : "l"(p), "r"((uint32_t)on) : "memory");
}
__device__ __forceinline__ uint32_t tag_of(unsigned long long v) { return (uint32_t)(v >> 32); }
__device__ __forceinline__ uint32_t nz_bits(float v) {
    const uint32_t u = __float_as_uint(v);
    return u == 0u ? 0x80000000u : u;
}
__device__ __forceinline__ void st_w(uint32_t* p, float v) {
    asm volatile("st.relaxed.gpu.global.b32 [%0], %1;" ::"l"(p), "r"(nz_bits(v)) : "memory");
}
__device__ __forceinline__ void st_w2(uint32_t* p, float a, float b) {
    asm volatile("st.relaxed.gpu.global.v2.b32 [%0], {%1, %2};" ::"l"(p), "r"(nz_bits(a)), "r"(nz_bits(b)) : "memory");
}
__device__ __forceinline__ void st_w4(uint32_t* p, const float (&v)[4]) {
    asm volatile("st.relaxed.gpu.global.v4.b32 [%0], {%1, %2, %3, %4};" ::"l"(p), "r"(nz_bits(v[0])), "r"(nz_bits(v[1])),
                 "r"(nz_bits(v[2])), "r"(nz_bits(v[3])) : "memory");
}
__device__ __forceinline__ void st_zero4(uint32_t* p, bool on) {
    asm volatile("{\n.reg .pred p;\nsetp.ne.u32 p, %1, 0;\n@p st.relaxed.gpu.global.v4.b32 [%0], {%2, %2, %2, %2};\n}"
                 ::"l"(p), "r"((uint32_t)on), "r"(0u) : "memory");
}
__device__ __forceinline__ void poll_w4(uint4& v, const uint32_t* p, uint32_t mn) {
    asm volatile("{\n.reg .pred p;\nsetp.eq.u32 p, %5, 0;\n@p ld.relaxed.gpu.global.v4.b32 {%0, %1, %2, %3}, [%4];\n}"
                 : "+r"(v.x), "+r"(v.y), "+r"(v.z), "+r"(v.w) : "l"(p), "r"(mn) : "memory");
}
__device__ __forceinline__ void poll_w2(uint2& v, const uint32_t* p, uint32_t mn) {
    asm volatile("{\n.reg .pred p;\nsetp.eq.u32 p, %3, 0;\n@p ld.relaxed.gpu.global.v2.b32 {%0, %1}, [%2];\n}"
                 : "+r"(v.x), "+r"(v.y) : "l"(p), "r"(mn) : "memory");
}
__device__ __forceinline__ uint32_t min4(const uint4& v) { return min(min(v.x, v.y), min(v.z, v.w)); }

__device__ __forceinline__ float bf_lo(uint32_t u) { return __uint_as_float(u << 16); }
__device__ __forceinline__ float bf_hi(uint32_t u) { return __uint_as_float(u & 0xffff0000u); }
__device__ __forceinline__ float bf_round(float x) { return __bfloat162float(__float2bfloat16_rn(x)); }
__device__ __forceinline__ float ex2(float x) {
    float y;
    asm("ex2.approx.ftz.f32 %0, %1;" : "=f"(y) : "f"(x));
    return y;
}
__device__ __forceinline__ float sigmoidf_(float x) { return 1.0f / (1.0f + __expf(-x)); }
__device__ __forceinline__ float warp_max(float v) {
    int i = __float_as_int(v);
    i ^= (i >> 31) & 0x7fffffff;
    i = __reduce_max_sync(0xffffffffu, i);
    i ^= (i >> 31) & 0x7fffffff;
    return __int_as_float(i);
}
__device__ __forceinline__ void fma8(float (&acc)[8], const uint4& w, float s) {
    acc[0] = fmaf(s, bf_lo(w.x), acc[0]); acc[1] = fmaf(s, bf_hi(w.x), acc[1]);
    acc[2] = fmaf(s, bf_lo(w.y), acc[2]); acc[3] = fmaf(s, bf_hi(w.y), acc[3]);
    acc[4] = fmaf(s, bf_lo(w.z), acc[4]); acc[5] = fmaf(s, bf_hi(w.z), acc[5]);
    acc[6] = fmaf(s, bf_lo(w.w), acc[6]); acc[7] = fmaf(s, bf_hi(w.w), acc[7]);
}
__device__ __forceinline__ float dot8(const uint4& w, const float (&q)[8]) {
    float a = q[0] * bf_lo(w.x), b = q[1] * bf_hi(w.x);
    a = fmaf(q[2], bf_lo(w.y), a); b = fmaf(q[3], bf_hi(w.y), b);
    a = fmaf(q[4], bf_lo(w.z), a); b = fmaf(q[5], bf_hi(w.z), b);
    a = fmaf(q[6], bf_lo(w.w), a); b = fmaf(q[7], bf_hi(w.w), b);
    return a + b;
}
__device__ __forceinline__ float2 reduce16(const float (&a0)[8], const float (&a1)[8], int lane) {
    float a[8], b[4];
    const bool h4 = lane & 16, h3 = lane & 8, h2 = lane & 4;
#pragma unroll
    for (int i = 0; i < 8; i++) a[i] = (h4 ? a1[i] : a0[i]) + __shfl_xor_sync(0xffffffffu, h4 ? a0[i] : a1[i], 16);
#pragma unroll
    for (int i = 0; i < 4; i++) b[i] = (h3 ? a[i + 4] : a[i]) + __shfl_xor_sync(0xffffffffu, h3 ? a[i] : a[i + 4], 8);
    return make_float2((h2 ? b[2] : b[0]) + __shfl_xor_sync(0xffffffffu, h2 ? b[0] : b[2], 4),
                       (h2 ? b[3] : b[1]) + __shfl_xor_sync(0xffffffffu, h2 ? b[1] : b[3], 4));
}

template <int N>
__device__ __forceinline__ void gather_q(float* s_q, int first, int stride, uint32_t tag) {
    unsigned long long a[N], b[N];
#pragma unroll
    for (int i = 0; i < N; i++) { a[i] = 0; b[i] = 0; }
#pragma unroll 1
    for (unsigned n = 0;; n++) {
#pragma unroll
        for (int i = 0; i < N; i++) ld_ll2(a[i], b[i], &g_q[first + i * stride], tag_of(a[i]) != tag || tag_of(b[i]) != tag);
        bool ok = true;
#pragma unroll
        for (int i = 0; i < N; i++) ok = ok && tag_of(a[i]) == tag && tag_of(b[i]) == tag;
        if (ok) break;
        if (n > SPIN_LIMIT) __trap();
    }
#pragma unroll
    for (int i = 0; i < N; i++) {
        const uint32_t x0 = (uint32_t)a[i], x1 = (uint32_t)b[i];
        *(float4*)&s_q[(first + i * stride) * 2] = make_float4(bf_lo(x0), bf_hi(x0), bf_lo(x1), bf_hi(x1));
    }
}

__device__ __forceinline__ float combine(int jp, int sl, int jw, int lane, int G, float* scratch) {
    const int row = jw * 4 + (lane >> 3);
    const uint32_t* rp = &g_rec[(jp * MAXG + lane) * 8];
    uint32_t* pp = part_row(jp, row) + sl * 32 + (lane & 7) * 4;
    uint2 rec[RK];
    uint4 dv[DK];
    uint32_t rm[RK], dm[DK];
#pragma unroll
    for (int k = 0; k < RK; k++) {
        rec[k] = make_uint2(0xff800000u, 0x80000000u);
        rm[k] = k * 32 + lane < G ? 0u : 1u;
    }
#pragma unroll
    for (int k = 0; k < DK; k++) {
        dv[k] = make_uint4(0u, 0u, 0u, 0u);
        dm[k] = k * 16 + row < G ? 0u : 1u;
    }
#pragma unroll 1
    for (unsigned n = 0;; n++) {
#pragma unroll
        for (int k = 0; k < RK; k++) poll_w2(rec[k], rp + k * 32 * 8, rm[k]);
#pragma unroll
        for (int k = 0; k < DK; k++) poll_w4(dv[k], pp + (size_t)k * 16 * kDH, dm[k]);
        uint32_t mn = 1u;
#pragma unroll
        for (int k = 0; k < RK; k++) { rm[k] = min(rec[k].x, rec[k].y); mn = min(mn, rm[k]); }
#pragma unroll
        for (int k = 0; k < DK; k++) { dm[k] = max(dm[k], min4(dv[k])); mn = min(mn, dm[k]); }
        if (__all_sync(0xffffffffu, mn != 0u)) break;
        if (n > SPIN_LIMIT) __trap();
    }
    float M = __uint_as_float(rec[0].x);
#pragma unroll
    for (int k = 1; k < RK; k++) M = fmaxf(M, __uint_as_float(rec[k].x));
    M = warp_max(M);
    float wt[RK], L = 0.f, a0 = 0.f, a1 = 0.f, a2 = 0.f, a3 = 0.f;
#pragma unroll
    for (int k = 0; k < RK; k++) {
        wt[k] = ex2(__uint_as_float(rec[k].x) - M);
        L = fmaf(wt[k], __uint_as_float(rec[k].y), L);
    }
#pragma unroll
    for (int k = 0; k < DK; k++) {
        const float wk = __shfl_sync(0xffffffffu, wt[k >> 1], (k & 1) * 16 + row);
        a0 = fmaf(wk, __uint_as_float(dv[k].x), a0);
        a1 = fmaf(wk, __uint_as_float(dv[k].y), a1);
        a2 = fmaf(wk, __uint_as_float(dv[k].z), a2);
        a3 = fmaf(wk, __uint_as_float(dv[k].w), a3);
    }
#pragma unroll
    for (int x = 8; x <= 16; x <<= 1) {
        a0 += __shfl_xor_sync(0xffffffffu, a0, x); a1 += __shfl_xor_sync(0xffffffffu, a1, x);
        a2 += __shfl_xor_sync(0xffffffffu, a2, x); a3 += __shfl_xor_sync(0xffffffffu, a3, x);
    }
    if (lane < 8) *(float4*)&scratch[jw * 32 + lane * 4] = make_float4(a0, a1, a2, a3);
#pragma unroll
    for (int x = 16; x; x >>= 1) L += __shfl_xor_sync(0xffffffffu, L, x);
    bar_sync(1, NJT);
    float acc = 0.f;
#pragma unroll
    for (int i = 0; i < NJW; i++) acc += scratch[i * 32 + lane];
#pragma unroll
    for (int k = 0; k < DK; k++) st_zero4(pp + (size_t)k * 16 * kDH, jp < EAGER && k * 16 + row < G);
    return bf_round(__fdividef(acc, L));
}

struct Params {
    const __nv_bfloat16 *x, *kc, *vc, *wq, *wo, *wg, *wu, *wd, *gw;
    __nv_bfloat16* out;
};

__global__ void __launch_bounds__(NTHREADS, 1) fused_kernel(const Params P, const __grid_constant__ CUtensorMap map_q,
                                                           const __grid_constant__ CUtensorMap map_g,
                                                           const __grid_constant__ CUtensorMap map_u) {
    extern __shared__ __align__(1024) unsigned char sm[];
    const int tid = threadIdx.x, lane = tid & 31, wid = tid >> 5;
    const int cta = blockIdx.x, G = gridDim.x;
    const uint32_t sbase = smem_u32(sm);
    const uint32_t barK = sbase + SM_BAR, barV = barK + 8 * NSTAGE, barE = barV + 8 * NSTAGE;
    const uint32_t barX = barE + 8 * NSTAGE;
    const uint32_t barG = barX + 8;
    const uint32_t barW = barG + 8;
    const uint32_t barD = barW + 8;
    const uint32_t barI = barD + 8;
    const uint32_t barQ = barI + 8;
    const uint32_t barH = barQ + 8;
    const uint32_t barJ = barH + 8;
    volatile int* s_item = (volatile int*)(sm + SM_ITEM);
    volatile int* s_cur = (volatile int*)(sm + SM_MISC);
    float* s_misc = (float*)(sm + SM_MISC);
    float2* s_v = (float2*)(sm + SM_V);
    const int gjob = cta >= NOJOB ? cta - NOJOB : (cta + (G - NOJOB) < NGJOB ? cta + (G - NOJOB) : -1);

    uint64_t pol;
    asm volatile("createpolicy.fractional.L2::evict_first.b64 %0, 1.0;" : "=l"(pol));
    auto issue_static = [&](int n) {
        const int i = n >> 1, item = i * G + cta;
        const uint32_t bar = ((n & 1) ? barV : barK) + 8 * i;
        if (!(n & 1)) s_item[i] = item;
        mbar_expect_tx(bar, TILE);
        bulk_g2s(sbase + SM_RING + n * TILE, ((n & 1) ? P.vc : P.kc) + (size_t)item * (TK * kDH), TILE, bar, pol);
    };
    if (__builtin_expect(tid == 0, 1)) {
        mbar_init(barX, 1);
#pragma unroll
        for (int s = 0; s < NFIRST; s++) {
            mbar_init(barK + 8 * s, 1);
            mbar_init(barV + 8 * s, 1);
        }
        fence_proxy_async();
        mbar_expect_tx(barX, (cta < NOJOB ? kD * 64 : 0) + kB * kD * 2 + kD * 2 + 16);
        if (cta < NOJOB) {
            tma_2d(sbase + SM_W, &map_q, cta * 32, 0, barX, pol);
            tma_2d(sbase + SM_W + 224 * 64, &map_q, cta * 32, 224, barX, pol);
        }
        bulk_g2s(sbase + SM_X, P.x, kB * kD * 2, barX);
        bulk_g2s(sbase + SM_GW, P.gw, kD * 2, barX);
        bulk_g2s(sbase + SM_EP, g_epoch, 16, barX);
#pragma unroll
        for (int n = 0; n < INFL; n++) issue_static(n);
#pragma unroll
        for (int s = 0; s < NSTAGE; s++) {
            if (s >= NFIRST) {
                mbar_init(barK + 8 * s, 1);
                mbar_init(barV + 8 * s, 1);
            }
            mbar_init(barE + 8 * s, NCW);
        }
        mbar_init(barG, 1);
        mbar_init(barW, 1);
        mbar_init(barD, 1);
        mbar_init(barI, 1);
        mbar_init(barQ, NJW);
        mbar_init(barH, 1);
        mbar_init(barJ, 1);
        *s_cur = -1;
        fence_proxy_async();
    }
    __syncthreads();

    if (wid == 0) {
        if (lane != 0) return;
        auto landed = [&](int n) {
            mbar_wait(((n & 1) ? barV : barK) + 8 * ((n >> 1) % NSTAGE), ((n >> 1) / NSTAGE) & 1);
        };
        landed(0);
        issue_static(INFL);
        unsigned next = (unsigned)((NFIRST - NSTATIC) * G + cta);
        bool wo_issued = cta >= NOJOB;
        const unsigned wo_item = gjob >= 0 ? NITEMS : (unsigned)((cta >> 3) - 1) * IPP;
        int i = NFIRST;
#pragma unroll 1
        for (;; i++) {
            const int s = i % NSTAGE;
            if (i >= NSTAGE) mbar_wait(barE + 8 * s, ((i / NSTAGE) - 1) & 1);
            const unsigned item = next + NSTATIC * G;
            if (item >= (unsigned)NITEMS) break;
            const size_t off = (size_t)item * (TK * kDH);
            landed(2 * i - INFL);
            s_item[s] = (int)item;
            mbar_expect_tx(barK + 8 * s, TILE);
            bulk_g2s(sbase + SM_RING + s * 2 * TILE, P.kc + off, TILE, barK + 8 * s, pol);
            if (i + 1 < NSTATIC) next = (unsigned)((i + 1 - NSTATIC) * G + cta);
            else next = atom_inc(g_ticket);
            if (!wo_issued && item >= wo_item) {
                wo_issued = true;
                mbar_expect_tx(barW, 32 * kD * 2);
                bulk_g2s(sbase + SM_W, P.wo + (size_t)cta * 32 * kD, 32 * kD * 2, barW, pol);
            }
            landed(2 * i + 1 - INFL);
            mbar_expect_tx(barV + 8 * s, TILE);
            bulk_g2s(sbase + SM_RING + s * 2 * TILE + TILE, P.vc + off, TILE, barV + 8 * s, pol);
        }
        s_item[i % NSTAGE] = -1;
        mbar_arrive(barK + 8 * (i % NSTAGE));
        if (!wo_issued) {
            if (gjob >= 0) mbar_wait(barH, 0);
            landed(2 * i - 3);
            mbar_expect_tx(barW, 32 * kD * 2);
            bulk_g2s(sbase + SM_W, P.wo + (size_t)cta * 32 * kD, 16 * kD * 2, barW, pol);
            landed(2 * i - 2);
            bulk_g2s(sbase + SM_W + 16 * kD * 2, P.wo + (size_t)(cta * 32 + 16) * kD, 16 * kD * 2, barW, pol);
        }
        if (gjob >= 0) {
            landed(2 * i - 1);
            mbar_expect_tx(barD, 16 * kD * 2);
            bulk_g2s(sbase + SM_RING + (i % NSTAGE) * 2 * TILE, P.wd + (size_t)gjob * 16 * kD, 16 * kD * 2, barD, pol);
        }
        mbar_wait(barX, 0);
        if (atom_inc(g_done) == (unsigned)G - 1) {
            g_ticket[0] = 0;
            g_done[0] = 0;
            g_epoch[0] = *(const unsigned*)(sm + SM_EP) + 1;
        }
        return;
    }

    if (wid <= NJW) {
        const int jt = tid - 32, jw = wid - 1;
        float* s_js = (float*)(sm + SM_JS);
        st_zero4(&g_y[(size_t)cta * (kB * kD) + jt * 4], true);
        st_zero4(&g_y[(size_t)cta * (kB * kD) + (NJT + jt) * 4], NJT + jt < kB * kD / 4);
        st_zero4(&g_rec[((jt >> 1) * MAXG + cta) * 8 + (jt & 1) * 4], jt < 2 * kPairs);
#pragma unroll
        for (int i = jt; i < (kPairs - EAGER) * 64; i += NJT)
            st_zero4(part_row(EAGER + (i >> 6), cta) + (i & 63) * 4, true);
        mbar_wait(barX, 0);
        const uint32_t tag = (*(const unsigned*)(sm + SM_EP) & 0x7fffffffu) + 1u;
        if (jw < 2) {
            float s = 0.f;
#pragma unroll
            for (int i = 0; i < kD / 32; i++)
                s += bf_round(lds_bf(sm + SM_X, jw * kD + i * 32 + lane) * lds_bf(sm + SM_GW, i * 32 + lane));
#pragma unroll
            for (int o = 16; o; o >>= 1) s += __shfl_xor_sync(0xffffffffu, s, o);
            const float g0 = bf_round(sigmoidf_(bf_round(s)));
            if (lane == 0) { s_misc[2 + jw] = g0; s_misc[4 + jw] = bf_round(1.0f - g0); }
        }
        bar_sync(1, NJT);
        if (jt == 0) {
            mbar_arrive(barI);
            asm volatile("fence.acq_rel.gpu;" ::: "memory");
            asm volatile("st.relaxed.gpu.global.u32 [%0], %1;" ::"l"(&g_init[cta]), "r"(tag) : "memory");
        }
        wait_ge(s_cur, 0, 200);
        gather_q<7>((float*)(sm + SM_Q), NCT * 2 + jt * 2, NJT * 2, tag);
        gather_q<7>((float*)(sm + SM_Q), NCT * 2 + 7 * NJT * 2 + jt * 2, NJT * 2, tag);
        __syncwarp();
        if (lane == 0) mbar_arrive(barQ);
#pragma unroll 1
        for (unsigned n = 0;; n++) {
            bool ok = true;
#pragma unroll
            for (int k = 0; k < RK; k++) {
                unsigned v = tag;
                if (k * 32 + lane < G)
                    asm volatile("ld.relaxed.gpu.global.u32 %0, [%1];" : "=r"(v) : "l"(&g_init[k * 32 + lane]) : "memory");
                ok = ok && v == tag;
            }
            if (__all_sync(0xffffffffu, ok)) break;
            __nanosleep(500);
            if (n > SPIN_LIMIT) __trap();
        }
        asm volatile("fence.acq_rel.gpu;" ::: "memory");
        if (gjob >= 0) {
            wait_ge(s_cur, 1 + (gjob >> 3), 200);
            if (jt == 0) {
                mbar_expect_tx(barG, 2 * 16 * kD * 2);
                tma_2d(sbase + SM_W, &map_g, gjob * 16, 0, barG, pol);
                tma_2d(sbase + SM_W + 224 * 32, &map_g, gjob * 16, 224, barG, pol);
                tma_2d(sbase + SM_W + 448 * 32, &map_u, gjob * 16, 0, barG, pol);
                tma_2d(sbase + SM_W + 672 * 32, &map_u, gjob * 16, 224, barG, pol);
            }
            const int rg = jt >> 2, ch = jt & 3;
            mbar_wait(barG, 0);
            float a0[8] = {}, a1[8] = {};
            const uint32_t ga = sbase + SM_W + (ch >> 1) * (kD * 32) + rg * 32 + (ch & 1) * 16;
#pragma unroll 2
            for (int k = 0; k < 14; k++) {
                const uint4 wv = lds128(ga + k * 32 * 32);
                fma8(a0, wv, lds_bf(sm + SM_X, k * 32 + rg));
                fma8(a1, wv, lds_bf(sm + SM_X, kD + k * 32 + rg));
            }
            *(float2*)&s_js[jw * 64 + (lane >> 4) * 32 + ch * 8 + ((lane >> 2) & 3) * 2] = reduce16(a0, a1, lane);
            bar_sync(1, NJT);
            if (jw == 0) {
                const int o = (lane >> 4) * 32 + (lane & 15);
                float g = 0.f, u = 0.f;
#pragma unroll
                for (int i = 0; i < NJW; i++) { g += s_js[i * 64 + o]; u += s_js[i * 64 + o + 16]; }
                const float hv = bf_round(bf_round(sigmoidf_(bf_round(g))) * bf_round(u));
                ((float*)&s_v[32 + (lane & 15)])[lane >> 4] = hv * s_misc[4 + (lane >> 4)];
                if (lane == 0) mbar_arrive(barH);
            }
        }
#pragma unroll 1
        for (int jb = 0; jb < (cta < NOJOB ? 2 : 0); jb++) {
            const int jp = jb * kH + (cta >> 3);
            wait_ge(s_cur, min(jp + JLAG, kPairs), 50);
            const float ov = combine(jp, cta & 7, jw, lane, G, s_js + (jb ^ 1) * (NJW * 64)) * s_misc[2 + jb];
            if (gjob >= 0) {
                if (jw == 0) ((float*)&s_v[lane])[jb] = ov;
            } else {
                const int gc = min(jw * 16 + (lane & 15), kD / 8 - 1), gh = lane >> 4;
                mbar_wait(barW, 0);
                float t[8] = {}, y[4];
                const uint32_t wa = sbase + SM_W + gh * 16 * (kD * 2) + gc * 16;
#pragma unroll
                for (int r = 0; r < 16; r++) fma8(t, lds128(wa + r * (kD * 2)), __shfl_sync(0xffffffffu, ov, gh * 16 + r));
#pragma unroll
                for (int i = 0; i < 4; i++)
                    y[i] = (gh ? t[i + 4] : t[i]) + __shfl_xor_sync(0xffffffffu, gh ? t[i] : t[i + 4], 16);
                if (jw * 16 + (lane & 15) < kD / 8) st_w4(&g_y[(size_t)cta * (kB * kD) + jb * kD + gc * 8 + gh * 4], y);
            }
        }
        if (jw == 0) {
            __syncwarp();
            if (lane == 0) mbar_arrive(barJ);
        }
        return;
    }

    const int ct = tid - 32 - NJT, w = wid - 1 - NJW;
    float* s_fl = (float*)(sm + SM_FL);
    float* s_ml = (float*)(sm + SM_ML);
    float* s_q = (float*)(sm + SM_Q);

    {
        const int rg = ct >> 2, ch = ct & 3;
        float a0[8] = {}, a1[8] = {};
        mbar_wait(barX, 0);
#pragma unroll
        for (int k = 0; k < 7; k++) {
            const uint4 wv = lds128(sbase + SM_W + (k * 64 + rg) * 64 + ch * 16);
            fma8(a0, wv, lds_bf(sm + SM_X, k * 64 + rg));
            fma8(a1, wv, lds_bf(sm + SM_X, kD + k * 64 + rg));
        }
        *(float2*)&s_fl[w * 64 + (lane >> 4) * 32 + ch * 8 + ((lane >> 2) & 3) * 2] = reduce16(a0, a1, lane);
    }
    bar_sync(2, NCT);
    const uint32_t tag = (*(const unsigned*)(sm + SM_EP) & 0x7fffffffu) + 1u;
    if (ct < 32 && cta < NOJOB) {
        float s0 = 0.f, s1 = 0.f;
#pragma unroll
        for (int i = 0; i < NCW; i++) {
            const float2 v = *(const float2*)&s_fl[i * 64 + 2 * ct];
            s0 += v.x; s1 += v.y;
        }
        const __nv_bfloat162 pk = __floats2bfloat162_rn(s0, s1);
        st_ll(&g_q[((ct >> 4) * kH + (cta >> 3)) * (kDH / 2) + (cta & 7) * 16 + (ct & 15)], *(const uint32_t*)&pk, tag);
    }
    gather_q<1>(s_q, ct * 2, 0, tag);
    bar_sync(2, NCT);
    mbar_wait(barI, 0);

    int fpar = 0, s = 0;
    {
        float q[8], o[8], m = 0.f, l = 0.f;
        int cur = -1, next_rec = 0;
#pragma unroll
        for (int j = 0; j < 8; j++) { q[j] = 0.f; o[j] = 0.f; }
        uint32_t ph = 0;
#pragma unroll 1
        for (;;) {
            mbar_wait(barK + 8 * s, ph);
            const int item = s_item[s];
            const int pair = item < 0 ? kPairs : item / IPP;
            if (pair != cur) {
                if (cur >= 0) {
                    float* fl = s_fl + fpar * (NCW * kDH);
                    float* ml = s_ml + fpar * (NCW * 2);
                    *(float4*)&fl[w * kDH + lane * 4] = make_float4(o[0], o[1], o[2], o[3]);
                    *(float4*)&fl[w * kDH + 128 + lane * 4] = make_float4(o[4], o[5], o[6], o[7]);
                    float lt = l;
#pragma unroll
                    for (int x = 16; x >= 32 / KPW; x >>= 1) lt += __shfl_xor_sync(0xffffffffu, lt, x);
                    if (lane == 0) *(float2*)&ml[w * 2] = make_float2(m, lt);
                    bar_sync(2, NCT);
                    float M = ml[0];
#pragma unroll
                    for (int i = 1; i < NCW; i++) M = fmaxf(M, ml[i * 2]);
                    float acc = 0.f, L = 0.f;
                    const int si = ((ct >> 2) & 1) * 128 + (ct >> 3) * 4 + (ct & 3);
#pragma unroll
                    for (int i = 0; i < NCW; i++) {
                        const float wt = ex2(ml[i * 2] - M);
                        acc = fmaf(wt, fl[i * kDH + si], acc);
                        L = fmaf(wt, ml[i * 2 + 1], L);
                    }
                    st_w(part_row(cur, cta) + ct, acc);
                    if (ct == 0) st_w2(&g_rec[(cur * MAXG + cta) * 8], M, L);
                    fpar ^= 1;
                    next_rec = cur + 1;
                }
#pragma unroll 1
                for (; next_rec < pair; next_rec++) {
                    st_w(part_row(next_rec, cta) + ct, 0.f);
                    if (ct == 0) st_w2(&g_rec[(next_rec * MAXG + cta) * 8], -INFINITY, 0.f);
                }
                if (ct == 0) *s_cur = pair;
                if (item < 0) break;
                cur = pair;
                if (pair >= QF) mbar_wait(barQ, 0);
                const float4 qa = *(const float4*)&s_q[pair * kDH + lane * 8];
                const float4 qb = *(const float4*)&s_q[pair * kDH + lane * 8 + 4];
                q[0] = qa.x; q[1] = qa.y; q[2] = qa.z; q[3] = qa.w;
                q[4] = qb.x; q[5] = qb.y; q[6] = qb.z; q[7] = qb.w;
                m = -3.0e38f; l = 0.f;
#pragma unroll
                for (int j = 0; j < 8; j++) o[j] = 0.f;
            }
            const uint32_t kaddr = sbase + SM_RING + s * 2 * TILE + w * KPW * 512 + lane * 16;
            float sc[KPW];
#pragma unroll
            for (int k = 0; k < KPW; k++) sc[k] = dot8(lds128(kaddr + k * 512), q);
            {
                int width = KPW, x = 16;
#pragma unroll
                for (; width > 1; width >>= 1, x >>= 1) {
                    const bool hi = lane & x;
#pragma unroll
                    for (int k = 0; k < width / 2; k++)
                        sc[k] = (hi ? sc[k + width / 2] : sc[k]) + __shfl_xor_sync(0xffffffffu, hi ? sc[k] : sc[k + width / 2], x);
                }
#pragma unroll
                for (; x >= 1; x >>= 1) sc[0] += __shfl_xor_sync(0xffffffffu, sc[0], x);
            }
            sc[0] = bf_round(sc[0]) * kScale;
            float mx = sc[0];
#pragma unroll
            for (int x = 16; x >= 32 / KPW; x >>= 1) mx = fmaxf(mx, __shfl_xor_sync(0xffffffffu, mx, x));
            const float mn = fmaxf(m, mx);
            const float corr = ex2(m - mn);
            const float p = ex2(sc[0] - mn);
            m = mn;
            l = fmaf(l, corr, p);
#pragma unroll
            for (int j = 0; j < 8; j++) o[j] *= corr;
            float pk[KPW];
#pragma unroll
            for (int k = 0; k < KPW; k++) pk[k] = __shfl_sync(0xffffffffu, p, k * (32 / KPW));
            mbar_wait(barV + 8 * s, ph);
#pragma unroll
            for (int k = 0; k < KPW; k++) fma8(o, lds128(kaddr + TILE + k * 512), pk[k]);
            __syncwarp();
            if (lane == 0) mbar_arrive(barE + 8 * s);
            if (++s == NSTAGE) { s = 0; ph ^= 1; }
        }
    }
    if (gjob < 0) return;

    {
        const int rq = lane >> 3, gc = min(w * 8 + (lane & 7), kD / 8 - 1);
        float a0[8] = {}, a1[8] = {}, y[4];
        mbar_wait(barJ, 0);
        if (cta < NOJOB) {
            mbar_wait(barW, 0);
            const uint32_t wa = sbase + SM_W + rq * 8 * (kD * 2) + gc * 16;
#pragma unroll
            for (int r = 0; r < 8; r++) {
                const uint4 wv = lds128(wa + r * (kD * 2));
                const float2 v = s_v[rq * 8 + r];
                fma8(a0, wv, v.x);
                fma8(a1, wv, v.y);
            }
        }
        mbar_wait(barD, 0);
        const uint32_t da = sbase + SM_RING + s * 2 * TILE + rq * 4 * (kD * 2) + gc * 16;
#pragma unroll
        for (int r = 0; r < 4; r++) {
            const uint4 wv = lds128(da + r * (kD * 2));
            const float2 v = s_v[32 + rq * 4 + r];
            fma8(a0, wv, v.x);
            fma8(a1, wv, v.y);
        }
        const bool h4 = lane & 16, h3 = lane & 8;
#pragma unroll
        for (int i = 0; i < 8; i++) a0[i] = (h4 ? a1[i] : a0[i]) + __shfl_xor_sync(0xffffffffu, h4 ? a0[i] : a1[i], 16);
#pragma unroll
        for (int i = 0; i < 4; i++) y[i] = (h3 ? a0[i + 4] : a0[i]) + __shfl_xor_sync(0xffffffffu, h3 ? a0[i] : a0[i + 4], 8);
        if (w < kD / 64) st_w4(&g_y[(size_t)cta * (kB * kD) + (lane >> 4) * kD + gc * 8 + ((lane >> 3) & 1) * 4], y);
    }
    {
        constexpr int YK = (MAXG + 127) / 128;
        const uint32_t* yp = &g_y[(size_t)(ct >> 1) * (kB * kD) + gjob * 8 + (ct & 1) * 4];
        uint4 dv[YK];
        uint32_t dm[YK];
#pragma unroll
        for (int k = 0; k < YK; k++) {
            dv[k] = make_uint4(0u, 0u, 0u, 0u);
            dm[k] = k * 128 + (ct >> 1) < G ? 0u : 1u;
        }
#pragma unroll 1
        for (unsigned n = 0;; n++) {
#pragma unroll
            for (int k = 0; k < YK; k++) poll_w4(dv[k], yp + (size_t)k * 128 * (kB * kD), dm[k]);
            uint32_t mn = 1u;
#pragma unroll
            for (int k = 0; k < YK; k++) { dm[k] = max(dm[k], min4(dv[k])); mn = min(mn, dm[k]); }
            if (__all_sync(0xffffffffu, mn != 0u)) break;
            if (n > SPIN_LIMIT) __trap();
        }
        float f0 = 0.f, f1 = 0.f, f2 = 0.f, f3 = 0.f;
#pragma unroll
        for (int k = 0; k < YK; k++) {
            f0 += __uint_as_float(dv[k].x); f1 += __uint_as_float(dv[k].y);
            f2 += __uint_as_float(dv[k].z); f3 += __uint_as_float(dv[k].w);
        }
        const bool h4 = lane & 16, h3 = lane & 8;
        const float u0 = (h4 ? f2 : f0) + __shfl_xor_sync(0xffffffffu, h4 ? f0 : f2, 16);
        const float u1 = (h4 ? f3 : f1) + __shfl_xor_sync(0xffffffffu, h4 ? f1 : f3, 16);
        float v = (h3 ? u1 : u0) + __shfl_xor_sync(0xffffffffu, h3 ? u0 : u1, 8);
        v += __shfl_xor_sync(0xffffffffu, v, 4);
        v += __shfl_xor_sync(0xffffffffu, v, 2);
        float* fl = s_fl + fpar * (NCW * kDH);
        if ((lane & 6) == 0) fl[w * 8 + (lane & 1) * 4 + (lane >> 4) * 2 + ((lane >> 3) & 1)] = v;
        bar_sync(2, NCT);
        if (ct < 8) {
            float t = 0.f;
#pragma unroll
            for (int i = 0; i < NCW; i++) t += fl[i * 8 + ct];
            P.out[gjob * 8 + ct] = __float2bfloat16_rn(t);
        }
    }
}

constexpr int FB_SPLITS = 32;
static_assert(kPairs * FB_SPLITS * 4 * (kDH + 2) <= kPairs * MAXG * kDH && 2 * kB * kHD + kB * kF <= MAXG * kB * kD, "scratch");
#define fb_q ((float*)g_s.y)
#define fb_o ((float*)g_s.y + kB * kHD)
#define fb_h ((float*)g_s.y + 2 * kB * kHD)
#define fb_part ((float*)g_s.part)

__global__ void fb_proj(const Params P) {
    const int i = blockIdx.x * blockDim.x + threadIdx.x;
    if (i < kB * kHD) {
        const int b = i / kHD, c = i % kHD;
        float s = 0.f;
        for (int d = 0; d < kD; d++) s = fmaf(__bfloat162float(P.x[b * kD + d]), __bfloat162float(P.wq[(size_t)d * kHD + c]), s);
        fb_q[i] = bf_round(s);
    } else if (i < kB * kHD + kB * kF) {
        const int j = i - kB * kHD, b = j / kF, f = j % kF;
        float g = 0.f, u = 0.f;
        for (int d = 0; d < kD; d++) {
            const float xv = __bfloat162float(P.x[b * kD + d]);
            g = fmaf(xv, __bfloat162float(P.wg[d * kF + f]), g);
            u = fmaf(xv, __bfloat162float(P.wu[d * kF + f]), u);
        }
        fb_h[j] = bf_round(bf_round(sigmoidf_(bf_round(g))) * bf_round(u));
    }
}
__global__ void fb_attn(const Params P) {
    const int pair = blockIdx.y, lane = threadIdx.x & 31, part = blockIdx.x * 4 + (threadIdx.x >> 5);
    constexpr int KEYS = kSK / (FB_SPLITS * 4);
    float q[8], o[8] = {}, m = -3.0e38f, l = 0.f;
#pragma unroll
    for (int j = 0; j < 8; j++) q[j] = fb_q[pair * kDH + lane * 8 + j];
    const size_t base = ((size_t)pair * kSK + (size_t)part * KEYS) * kDH + lane * 8;
    for (int k = 0; k < KEYS; k++) {
        float s = dot8(*(const uint4*)(P.kc + base + (size_t)k * kDH), q);
#pragma unroll
        for (int x = 16; x; x >>= 1) s += __shfl_xor_sync(0xffffffffu, s, x);
        s = bf_round(s) * kScale;
        const float mn = fmaxf(m, s), corr = ex2(m - mn), p = ex2(s - mn);
        m = mn;
        l = fmaf(l, corr, p);
#pragma unroll
        for (int j = 0; j < 8; j++) o[j] *= corr;
        fma8(o, *(const uint4*)(P.vc + base + (size_t)k * kDH), p);
    }
    float* dst = &fb_part[((size_t)pair * FB_SPLITS * 4 + part) * (kDH + 2)];
#pragma unroll
    for (int j = 0; j < 8; j++) dst[lane * 8 + j] = o[j];
    if (lane == 0) { dst[kDH] = m; dst[kDH + 1] = l; }
}
__global__ void fb_comb() {
    const float* src = &fb_part[(size_t)blockIdx.x * FB_SPLITS * 4 * (kDH + 2)];
    float M = -INFINITY, acc = 0.f, L = 0.f;
    for (int i = 0; i < FB_SPLITS * 4; i++) M = fmaxf(M, src[i * (kDH + 2) + kDH]);
    for (int i = 0; i < FB_SPLITS * 4; i++) {
        const float wt = ex2(src[i * (kDH + 2) + kDH] - M);
        acc = fmaf(wt, src[i * (kDH + 2) + threadIdx.x], acc);
        L = fmaf(wt, src[i * (kDH + 2) + kDH + 1], L);
    }
    fb_o[blockIdx.x * kDH + threadIdx.x] = bf_round(acc / L);
}
__global__ void fb_out(const Params P) {
    const int i = blockIdx.x * blockDim.x + threadIdx.x, b = i / kD, n = i % kD;
    float s = 0.f, a = 0.f, c = 0.f;
    for (int d = 0; d < kD; d++) s += bf_round(__bfloat162float(P.x[b * kD + d]) * __bfloat162float(P.gw[d]));
    const float g0 = bf_round(sigmoidf_(bf_round(s)));
    for (int j = 0; j < kHD; j++) a = fmaf(fb_o[b * kHD + j], __bfloat162float(P.wo[(size_t)j * kD + n]), a);
    for (int f = 0; f < kF; f++) c = fmaf(fb_h[b * kF + f], __bfloat162float(P.wd[f * kD + n]), c);
    P.out[i] = __float2bfloat16_rn(g0 * a + bf_round(1.0f - g0) * c);
}

typedef CUresult (*EncodeFn)(CUtensorMap*, CUtensorMapDataType, cuuint32_t, void*, const cuuint64_t*, const cuuint64_t*,
                             const cuuint32_t*, const cuuint32_t*, CUtensorMapInterleave, CUtensorMapSwizzle,
                             CUtensorMapL2promotion, CUtensorMapFloatOOBfill);

bool make_map(EncodeFn encode, CUtensorMap* map, const void* base, int cols, int box_cols) {
    const cuuint64_t dims[2] = {(cuuint64_t)cols, (cuuint64_t)kD};
    const cuuint64_t strides[1] = {(cuuint64_t)cols * 2};
    const cuuint32_t box[2] = {(cuuint32_t)box_cols, 224};
    const cuuint32_t es[2] = {1, 1};
    return encode(map, CU_TENSOR_MAP_DATA_TYPE_BFLOAT16, 2, const_cast<void*>(base), dims, strides, box, es,
                  CU_TENSOR_MAP_INTERLEAVE_NONE, CU_TENSOR_MAP_SWIZZLE_NONE, CU_TENSOR_MAP_L2_PROMOTION_L2_128B,
                  CU_TENSOR_MAP_FLOAT_OOB_FILL_NONE) == CUDA_SUCCESS;
}

}

extern "C" void kernel_launch(void* const* d_in, const int* in_sizes, int n_in, void* d_out, int out_size) {
    (void)in_sizes; (void)n_in; (void)out_size;
    static EncodeFn encode = nullptr;
    static int grid = -1;
    if (grid < 0) {
        int dev = 0, sms = 0, per_sm = 0;
        cudaGetDevice(&dev);
        cudaDeviceGetAttribute(&sms, cudaDevAttrMultiProcessorCount, dev);
        cudaDriverEntryPointQueryResult qr;
        void* fn = nullptr;
        if (cudaGetDriverEntryPoint("cuTensorMapEncodeTiled", &fn, cudaEnableDefault, &qr) == cudaSuccess) encode = (EncodeFn)fn;
        if (cudaFuncSetAttribute(fused_kernel, cudaFuncAttributeMaxDynamicSharedMemorySize, SM_TOTAL) == cudaSuccess)
            cudaOccupancyMaxActiveBlocksPerMultiprocessor(&per_sm, fused_kernel, NTHREADS, SM_TOTAL);
        (void)cudaGetLastError();
        grid = (encode && per_sm >= 1 && sms >= NOJOB) ? (sms < MAXG ? sms : MAXG) : 0;
    }
    Params P;
    P.x = (const __nv_bfloat16*)d_in[0];
    P.kc = (const __nv_bfloat16*)d_in[1];
    P.vc = (const __nv_bfloat16*)d_in[2];
    P.wq = (const __nv_bfloat16*)d_in[3];
    P.wo = (const __nv_bfloat16*)d_in[4];
    P.wg = (const __nv_bfloat16*)d_in[6];
    P.wu = (const __nv_bfloat16*)d_in[7];
    P.wd = (const __nv_bfloat16*)d_in[8];
    P.gw = (const __nv_bfloat16*)d_in[9];
    P.out = (__nv_bfloat16*)d_out;
    cudaStream_t st = cudaStreamPerThread;
    CUtensorMap map_q, map_g, map_u;
    if (grid > 0 && make_map(encode, &map_q, P.wq, kHD, 32) && make_map(encode, &map_g, P.wg, kF, 16) &&
        make_map(encode, &map_u, P.wu, kF, 16)) {
        fused_kernel<<<grid, NTHREADS, SM_TOTAL, st>>>(P, map_q, map_g, map_u);
        return;
    }
    grid = 0;
    fb_proj<<<(kB * kHD + kB * kF + 255) / 256, 256, 0, st>>>(P);
    fb_attn<<<dim3(FB_SPLITS, kPairs), 128, 0, st>>>(P);
    fb_comb<<<kPairs, 256, 0, st>>>();
    fb_out<<<7, 128, 0, st>>>(P);
}
```
